```python
import torch

def _softmax(x, axis=-1):
    return torch.softmax(x, dim=axis)

def _gelu(x):
    return torch.nn.functional.gelu(x, approximate='tanh')

def _silu(x):
    return torch.nn.functional.silu(x)

def _sigmoid(x):
    return torch.sigmoid(x)

def _layernorm(x, axis=-1, eps=1e-05):
    m = x.mean(dim=axis, keepdim=True)
    v = x.var(dim=axis, keepdim=True, unbiased=False)
    return (x - m) / torch.sqrt(v + eps)

def _scatter_add(tgt, idx, src, axis=0):
    return tgt.clone().index_add_(axis, idx, src)

def _segment_sum(src, seg, n):
    out = torch.zeros((n,) + src.shape[1:], dtype=src.dtype)
    return out.index_add_(0, seg, src)

def _pad(x, pw):
    flat = tuple((v for pair in reversed(pw) for v in pair))
    return torch.nn.functional.pad(x, flat)
kernel_name = 'gated_mix__memory_aug_recurrent_mem_tr__glu_gated_glu__prompt'

def setup_inputs():

    _w = lambda a: (lambda t: t.to(torch.bfloat16) if t.is_floating_point() else t)(torch.as_tensor(a))

    def _A_setup():
        B, S, Dm = (1, 2048, 640)
        H, Dh = (32, 192)
        M, seg = (8, 32)
        seg = min(seg, S)
        S = S // seg * seg
        return {'x': _w((lambda *s: torch.randn(*s, dtype=torch.bfloat16) * 0.05)(B, S, Dm)), 'mem0': _w((lambda *s: torch.randn(*s, dtype=torch.bfloat16) * 0.8)(B, M, Dm)), 'Wq': _w((lambda *s: torch.randn(*s, dtype=torch.bfloat16) * 1.6)(Dm, H, Dh) * Dm ** (-0.5)), 'Wk': _w((lambda *s: torch.randn(*s, dtype=torch.bfloat16) * 1.6)(Dm, H, Dh) * Dm ** (-0.5)), 'Wv': _w((lambda *s: torch.randn(*s, dtype=torch.bfloat16) * 0.8)(Dm, H, Dh) * Dm ** (-0.5)), 'Wo': _w((lambda *s: torch.randn(*s, dtype=torch.bfloat16) * 0.8)(H, Dh, Dm) * (H * Dh) ** (-0.5)), 'seg_len': seg}
    _A_in = _A_setup()

    def _B_setup():
        B, S, D, F = (1, 2048, 640, 1536)
        return {'x': _w((lambda *s: torch.randn(*s, dtype=torch.bfloat16) * 0.05)(B, S, D)), 'w_gate': _w((lambda *s: torch.randn(*s, dtype=torch.bfloat16) * 0.4)(D, F)), 'w_up': _w((lambda *s: torch.randn(*s, dtype=torch.bfloat16) * 0.05)(D, F)), 'w_down': _w((lambda *s: torch.randn(*s, dtype=torch.bfloat16) * 0.05)(F, D))}
    _B_in = _B_setup()
    return {'A_x': _A_in['x'], 'A_mem0': _A_in['mem0'], 'A_Wq': _A_in['Wq'], 'A_Wk': _A_in['Wk'], 'A_Wv': _A_in['Wv'], 'A_Wo': _A_in['Wo'], 'A_seg_len': _A_in['seg_len'], 'B_x': _B_in['x'], 'B_w_gate': _B_in['w_gate'], 'B_w_up': _B_in['w_up'], 'B_w_down': _B_in['w_down'], 'gate_w': _w((lambda *s: torch.randn(*s, dtype=torch.bfloat16) * 0.05)(640) * 16.0)}

def reference(A_x, A_mem0, A_Wq, A_Wk, A_Wv, A_Wo, A_seg_len, B_x, B_w_gate, B_w_up, B_w_down, gate_w):

    def _A_ref(x, mem0, Wq, Wk, Wv, Wo, seg_len):
        B, S, Dm = x.shape
        H, Dh = (Wq.shape[1], Wq.shape[2])
        M = mem0.shape[1]
        scale = Dh ** (-0.5)
        n_seg = S // seg_len
        L = M + seg_len
        idx = torch.arange(L)
        mask = (idx[:, None] < M) | (idx[:, None] >= idx[None, :])
        mem = mem0
        outs = []
        for s in range(n_seg):
            xs = x[:, s * seg_len:(s + 1) * seg_len, :].clone()
            h = torch.concatenate([mem, xs], axis=1)
            q = torch.einsum('btd,dhe->bhte', h, Wq)
            k = torch.einsum('btd,dhe->bhte', h, Wk)
            v = torch.einsum('btd,dhe->bhte', h, Wv)
            scores = torch.einsum('bhqe,bhke->bhqk', q, k) * scale
            scores = torch.where(mask[None, None], scores, -1000000000.0)
            p = _softmax(scores, axis=-1)
            o = torch.einsum('bhqk,bhke->bhqe', p, v)
            o = torch.einsum('bhte,hed->btd', o, Wo)
            mem = o[:, :M, :].clone()
            outs.append(o[:, M:, :])
        return torch.concatenate(outs, axis=1)

    def _B_ref(x, w_gate, w_up, w_down):
        g = torch.einsum('bsd,df->bsf', x, w_gate)
        u = torch.einsum('bsd,df->bsf', x, w_up)
        h = _sigmoid(g) * u
        return torch.einsum('bsf,fd->bsd', h, w_down)
    x = A_x
    g = _sigmoid((x * gate_w).sum(-1, keepdims=True))
    a = _A_ref(x, A_mem0, A_Wq, A_Wk, A_Wv, A_Wo, A_seg_len)
    b = _B_ref(x, B_w_gate, B_w_up, B_w_down)
    return g * a + (1 - g) * b
```

```cpp
#include <cuda_runtime.h>
#include <cuda_bf16.h>
#include <cuda.h>
#include <stdint.h>

#define DEVINL __device__ __forceinline__

DEVINL uint32_t smem_u32(const void* p) { return (uint32_t)__cvta_generic_to_shared(p); }

DEVINL void mbar_init(uint32_t bar, uint32_t count) {
  asm volatile("mbarrier.init.shared::cta.b64 [%0], %1;" ::"r"(bar), "r"(count) : "memory");
}
DEVINL void mbar_arrive(uint32_t bar) {
  asm volatile("mbarrier.arrive.shared::cta.b64 _, [%0];" ::"r"(bar) : "memory");
}
DEVINL void mbar_arrive_expect_tx(uint32_t bar, uint32_t bytes) {
  asm volatile("mbarrier.arrive.expect_tx.shared::cta.b64 _, [%0], %1;" ::"r"(bar), "r"(bytes) : "memory");
}
DEVINL bool mbar_try_wait(uint32_t bar, uint32_t parity) {
  uint32_t done;
  asm volatile(
      "{\n.reg .pred p;\nmbarrier.try_wait.parity.shared::cta.b64 p, [%1], %2;\nselp.u32 %0, 1, 0, p;\n}"
      : "=r"(done)
      : "r"(bar), "r"(parity)
      : "memory");
  return done != 0;
}
__device__ unsigned g_abort;
DEVINL void mbar_wait(uint32_t bar, uint32_t parity) {
  asm volatile(
      "{\n.reg .pred p;\n.reg .u32 n;\nmov.u32 n, 0;\n"
      "WAIT_LOOP:\n"
      "mbarrier.try_wait.parity.shared::cta.b64 p, [%0], %1;\n"
      "@p bra WAIT_DONE;\n"
      "add.u32 n, n, 1;\n"
      "setp.lt.u32 p, n, 16777216;\n"
      "@p bra WAIT_LOOP;\n"
      "trap;\n"
      "WAIT_DONE:\n}"
      ::"r"(bar), "r"(parity) : "memory");
}
DEVINL void bar_sync(int id, int n) { asm volatile("bar.sync %0, %1;" ::"r"(id), "r"(n) : "memory"); }
DEVINL void bar_arrive(int id, int n) { asm volatile("bar.arrive %0, %1;" ::"r"(id), "r"(n) : "memory"); }
DEVINL void fence_proxy_async() { asm volatile("fence.proxy.async.shared::cta;" ::: "memory"); }
DEVINL void fence_proxy_async_all() { asm volatile("fence.proxy.async;" ::: "memory"); }

DEVINL uint32_t mapa(uint32_t addr, uint32_t rank) {
  uint32_t r;
  asm volatile("mapa.shared::cluster.u32 %0, %1, %2;" : "=r"(r) : "r"(addr), "r"(rank));
  return r;
}
DEVINL void st_async_v4(uint32_t dst, uint32_t a, uint32_t b, uint32_t c, uint32_t d, uint32_t bar) {
  asm volatile("st.async.weak.shared::cluster.mbarrier::complete_tx::bytes.v4.u32 [%0], {%1,%2,%3,%4}, [%5];" ::"r"(dst),
               "r"(a), "r"(b), "r"(c), "r"(d), "r"(bar)
               : "memory");
}
DEVINL void st_async_v2(uint32_t dst, uint32_t a, uint32_t b, uint32_t bar) {
  asm volatile("st.async.weak.shared::cluster.mbarrier::complete_tx::bytes.v2.u32 [%0], {%1,%2}, [%3];" ::"r"(dst), "r"(a),
               "r"(b), "r"(bar)
               : "memory");
}
DEVINL void cluster_sync_all() {
  asm volatile("barrier.cluster.arrive.release.aligned;\nbarrier.cluster.wait.acquire.aligned;" ::: "memory");
}

DEVINL void tma_load_2d(uint32_t dst, const CUtensorMap* tm, int c0, int c1, uint32_t bar) {
  asm volatile(
      "cp.async.bulk.tensor.2d.shared::cluster.global.mbarrier::complete_tx::bytes [%0], [%1, {%3, %4}], [%2];" ::"r"(dst),
      "l"(tm), "r"(bar), "r"(c0), "r"(c1)
      : "memory");
}
DEVINL void tma_store_2d(const CUtensorMap* tm, uint32_t src, int c0, int c1) {
  asm volatile("cp.async.bulk.tensor.2d.global.shared::cta.bulk_group [%0, {%2, %3}], [%1];" ::"l"(tm), "r"(src), "r"(c0),
               "r"(c1)
               : "memory");
}
DEVINL void bulk_commit() { asm volatile("cp.async.bulk.commit_group;" ::: "memory"); }
DEVINL void bulk_wait_read0() { asm volatile("cp.async.bulk.wait_group.read 0;" ::: "memory"); }
DEVINL void bulk_wait0() { asm volatile("cp.async.bulk.wait_group 0;" ::: "memory"); }

DEVINL uint4 ld_rlx_v4(const void* p) {
  uint4 v;
  asm volatile("ld.relaxed.gpu.global.v4.u32 {%0,%1,%2,%3}, [%4];" : "=r"(v.x), "=r"(v.y), "=r"(v.z), "=r"(v.w) : "l"(p) : "memory");
  return v;
}
DEVINL void st_rlx_v4(void* p, uint32_t a, uint32_t b, uint32_t c, uint32_t d) {
  asm volatile("st.relaxed.gpu.global.v4.u32 [%0], {%1,%2,%3,%4};" ::"l"(p), "r"(a), "r"(b), "r"(c), "r"(d) : "memory");
}
DEVINL void st_rlx_u32(void* p, uint32_t a) { asm volatile("st.relaxed.gpu.global.u32 [%0], %1;" ::"l"(p), "r"(a) : "memory"); }
DEVINL uint32_t ld_acq_u32(const void* p) {
  uint32_t v;
  asm volatile("ld.acquire.gpu.global.u32 %0, [%1];" : "=r"(v) : "l"(p) : "memory");
  return v;
}
DEVINL void red_release_add(void* p, uint32_t v) {
  asm volatile("red.release.gpu.global.add.u32 [%0], %1;" ::"l"(p), "r"(v) : "memory");
}

DEVINL void red_relaxed_add(void* p, uint32_t v) {
  asm volatile("red.relaxed.gpu.global.add.u32 [%0], %1;" ::"l"(p), "r"(v) : "memory");
}
DEVINL void tma_prefetch_2d(const CUtensorMap* tm, int c0, int c1) {
  asm volatile("cp.async.bulk.prefetch.tensor.2d.L2.global [%0, {%1, %2}];" ::"l"(tm), "r"(c0), "r"(c1) : "memory");
}
DEVINL void ldsm_x4(uint32_t (&r)[4], uint32_t addr) {
  asm volatile("ldmatrix.sync.aligned.m8n8.x4.shared.b16 {%0,%1,%2,%3}, [%4];" : "=r"(r[0]), "=r"(r[1]), "=r"(r[2]), "=r"(r[3]) : "r"(addr) : "memory");
}
DEVINL void ldsm_x4_t(uint32_t (&r)[4], uint32_t addr) {
  asm volatile("ldmatrix.sync.aligned.m8n8.x4.trans.shared.b16 {%0,%1,%2,%3}, [%4];" : "=r"(r[0]), "=r"(r[1]), "=r"(r[2]), "=r"(r[3]) : "r"(addr) : "memory");
}
DEVINL void ldsm_x2(uint32_t& r0, uint32_t& r1, uint32_t addr) {
  asm volatile("ldmatrix.sync.aligned.m8n8.x2.shared.b16 {%0,%1}, [%2];" : "=r"(r0), "=r"(r1) : "r"(addr) : "memory");
}
DEVINL void ldsm_x1(uint32_t& r0, uint32_t addr) {
  asm volatile("ldmatrix.sync.aligned.m8n8.x1.shared.b16 {%0}, [%1];" : "=r"(r0) : "r"(addr) : "memory");
}
DEVINL void mma16816(float (&d)[4], uint32_t a0, uint32_t a1, uint32_t a2, uint32_t a3, uint32_t b0, uint32_t b1) {
  asm volatile("mma.sync.aligned.m16n8k16.row.col.f32.bf16.bf16.f32 {%0,%1,%2,%3}, {%4,%5,%6,%7}, {%8,%9}, {%0,%1,%2,%3};"
               : "+f"(d[0]), "+f"(d[1]), "+f"(d[2]), "+f"(d[3])
               : "r"(a0), "r"(a1), "r"(a2), "r"(a3), "r"(b0), "r"(b1));
}
DEVINL void mma1688(float (&d)[4], uint32_t a0, uint32_t a1, uint32_t b0) {
  asm volatile("mma.sync.aligned.m16n8k8.row.col.f32.bf16.bf16.f32 {%0,%1,%2,%3}, {%4,%5}, {%6}, {%0,%1,%2,%3};"
               : "+f"(d[0]), "+f"(d[1]), "+f"(d[2]), "+f"(d[3])
               : "r"(a0), "r"(a1), "r"(b0));
}
DEVINL uint32_t pack_bf16(float lo, float hi) {
  uint32_t r;
  asm("cvt.rn.bf16x2.f32 %0, %1, %2;" : "=r"(r) : "f"(hi), "f"(lo));
  return r;
}
DEVINL void wg_fence() { asm volatile("wgmma.fence.sync.aligned;" ::: "memory"); }
DEVINL void wg_commit() { asm volatile("wgmma.commit_group.sync.aligned;" ::: "memory"); }
template <int N>
DEVINL void wg_wait() { asm volatile("wgmma.wait_group.sync.aligned %0;" ::"n"(N) : "memory"); }

DEVINL uint64_t make_desc(uint32_t addr, uint32_t lbo, uint32_t sbo, uint32_t swz) {
  return (uint64_t)((addr & 0x3FFFF) >> 4) | ((uint64_t)(lbo >> 4) << 16) | ((uint64_t)(sbo >> 4) << 32) | ((uint64_t)swz << 62);
}

#define SKIP_BULK 0
constexpr int SEQ = 2048, DM = 640, NH = 32, DH = 192, MM = 8, SEG = 32, NSEG = 64, HD = NH * DH, FF = 1536;
constexpr int NSLOT = 4, NREP = 8, NUNIT = 80;
constexpr int XST = 5;
#define VSPLIT 40

__device__ __nv_bfloat16 g_q[SEQ * HD];
__device__ __nv_bfloat16 g_k[NSEG * 40 * HD];
__device__ __nv_bfloat16 g_vT[NSEG * HD * 40];
constexpr uint32_t H1_SLOT = NH * NUNIT * 128, H2_SLOT = NREP * NUNIT * 128, H2_BASE = NSLOT * H1_SLOT;
__device__ uint4 g_xch[(H2_BASE + NSLOT * H2_SLOT) / 16];
__device__ unsigned g_segflag[NSEG];

constexpr int OFF_WV = 0;
constexpr int OFF_WO = 81920;
constexpr int OFF_X = 163840;
constexpr int OFF_KT = OFF_X + XST * 4096;
constexpr int OFF_QX = OFF_KT + 5120;
constexpr int OFF_T9 = OFF_QX + 4096;
constexpr int OFF_MEM = OFF_T9 + 6144;
constexpr int OFF_VT = OFF_MEM + 10240;
constexpr int OFF_QM = OFF_VT + 5248;
constexpr int OFF_SM = OFF_QM + 1024;
constexpr int OFF_OM = OFF_SM + 3840;
constexpr int OFF_BAR = OFF_OM + 3072;
constexpr int OFF_P = OFF_BAR + 256;
constexpr int OFF_DBG = OFF_P + 640;
constexpr int MAIN_SMEM = OFF_DBG + 128;
static_assert(MAIN_SMEM <= 232448, "smem");
static_assert(OFF_KT % 1024 == 0 && OFF_QX % 1024 == 0, "align");

enum { B_XFULL = 0, B_XEMPTY = XST, B_W = 2 * XST, B_MEM, B_SM, B_OM, B_T9, B_COUNT };

#define TSW(cond, idx)
#define DBGV(cond, idx, val) do { if (cond) asm volatile("st.shared.u32 [%0], %1;" :: "r"(sb + OFF_DBG + (idx) * 4), "r"((uint32_t)(val)) : "memory"); } while (0)
#define DBGADD(cond, idx, val)
#define TS(idx) TSW(s == 20 && lane == 0 && wid == 0, idx)
#define TSX(idx) TSW(x == 20 && lane == 0, idx)
struct MainParams {
  CUtensorMap tm_x, tm_wv, tm_wo, tm_q, tm_k, tm_v;
  const __nv_bfloat16* wq;
  const __nv_bfloat16* wk;
  const __nv_bfloat16* mem0;
  int d1, d2, d3, skip;
};

constexpr uint32_t DHI_SW128 = (1024u >> 4) | (1u << 30);
constexpr uint32_t DHI_NONE = (128u >> 4);
DEVINL uint32_t desc_lo(uint32_t addr, uint32_t lbo) { return ((addr & 0x3FFFF) >> 4) | ((lbo >> 4) << 16); }

template <int OFFB, int SCALE_D>
DEVINL void wgmma_rs_n32(float (&d)[16], uint32_t a0, uint32_t a1, uint32_t a2, uint32_t a3, uint32_t blo) {
  asm volatile(
      "{\n.reg .b64 db;\n.reg .b32 lo;\n.reg .pred p;\nsetp.ne.u32 p, %23, 0;\nadd.u32 lo, %20, %21;\nmov.b64 db, {lo, %22};\n"
      "wgmma.mma_async.sync.aligned.m64n32k16.f32.bf16.bf16 "
      "{%0,%1,%2,%3,%4,%5,%6,%7,%8,%9,%10,%11,%12,%13,%14,%15}, {%16,%17,%18,%19}, db, p, 1, 1, 0;\n}"
      : "+f"(d[0]), "+f"(d[1]), "+f"(d[2]), "+f"(d[3]), "+f"(d[4]), "+f"(d[5]), "+f"(d[6]), "+f"(d[7]), "+f"(d[8]),
        "+f"(d[9]), "+f"(d[10]), "+f"(d[11]), "+f"(d[12]), "+f"(d[13]), "+f"(d[14]), "+f"(d[15])
      : "r"(a0), "r"(a1), "r"(a2), "r"(a3), "r"(blo), "n"(OFFB >> 4), "n"(DHI_SW128), "n"(SCALE_D));
}
template <int OFFA, int OFFB, int SCALE_D>
DEVINL void wgmma_ss_n32_tA(float (&d)[16], uint32_t alo, uint32_t blo) {
  asm volatile(
      "{\n.reg .b64 da, db;\n.reg .b32 lo;\n.reg .pred p;\nsetp.ne.u32 p, %21, 0;\nadd.u32 lo, %16, %18;\nmov.b64 da, {lo, %20};\n"
      "add.u32 lo, %17, %19;\nmov.b64 db, {lo, %20};\n"
      "wgmma.mma_async.sync.aligned.m64n32k16.f32.bf16.bf16 "
      "{%0,%1,%2,%3,%4,%5,%6,%7,%8,%9,%10,%11,%12,%13,%14,%15}, da, db, p, 1, 1, 1, 0;\n}"
      : "+f"(d[0]), "+f"(d[1]), "+f"(d[2]), "+f"(d[3]), "+f"(d[4]), "+f"(d[5]), "+f"(d[6]), "+f"(d[7]), "+f"(d[8]),
        "+f"(d[9]), "+f"(d[10]), "+f"(d[11]), "+f"(d[12]), "+f"(d[13]), "+f"(d[14]), "+f"(d[15])
      : "r"(alo), "r"(blo), "n"(OFFA >> 4), "n"(OFFB >> 4), "n"(DHI_SW128), "n"(SCALE_D));
}
template <int OFFA, int OFFB, int TB, int SCALE_D>
DEVINL void wgmma_ss_n8_tA(float (&d)[4], uint32_t alo, uint32_t blo) {
  asm volatile(
      "{\n.reg .b64 da, db;\n.reg .b32 lo;\n.reg .pred p;\nsetp.ne.u32 p, %11, 0;\nadd.u32 lo, %4, %6;\nmov.b64 da, {lo, %8};\n"
      "add.u32 lo, %5, %7;\nmov.b64 db, {lo, %9};\n"
      "wgmma.mma_async.sync.aligned.m64n8k16.f32.bf16.bf16 {%0,%1,%2,%3}, da, db, p, 1, 1, 1, %10;\n}"
      : "+f"(d[0]), "+f"(d[1]), "+f"(d[2]), "+f"(d[3])
      : "r"(alo), "r"(blo), "n"(OFFA >> 4), "n"(OFFB >> 4), "n"(DHI_SW128), "n"(DHI_NONE), "n"(TB), "n"(SCALE_D));
}
template <int N> struct IC { static constexpr int value = N; };
template <int I, int N, class F> DEVINL void static_for(F&& f) {
  if constexpr (I < N) { f(IC<I>{}); static_for<I + 1, N>(f); }
}

DEVINL uint32_t enc_neg(uint32_t w) {
  uint32_t t = w ^ 0x80008000u;
  return t ? t : 0x80008000u;
}

DEVINL float ex2f(float x) { float y; asm("ex2.approx.ftz.f32 %0, %1;" : "=f"(y) : "f"(x)); return y; }
DEVINL float rcpf(float x) { float y; asm("rcp.approx.ftz.f32 %0, %1;" : "=f"(y) : "f"(x)); return y; }
DEVINL void lds_v2(float& x, float& y, uint32_t a) { asm volatile("ld.shared.v2.f32 {%0,%1}, [%2];" : "=f"(x), "=f"(y) : "r"(a) : "memory"); }
DEVINL void lds_v4(float4& v, uint32_t a) { asm volatile("ld.shared.v4.f32 {%0,%1,%2,%3}, [%4];" : "=f"(v.x), "=f"(v.y), "=f"(v.z), "=f"(v.w) : "r"(a) : "memory"); }
DEVINL void sts_u32(uint32_t a, uint32_t v) { asm volatile("st.shared.u32 [%0], %1;" ::"r"(a), "r"(v) : "memory"); }
DEVINL uint32_t rmt(uint32_t addr, int rank) { return (addr & 0x00FFFFFFu) | ((uint32_t)rank << 24); }

template <int IS_K>
DEVINL void proj_wg(const MainParams& p, uint32_t sb, int h, int j, int wid  , int lane) {
  const __nv_bfloat16* W = IS_K ? p.wk : p.wq;
  uint32_t A[40][4];
  {
    const __nv_bfloat16* base = W + (size_t)h * DH + j * 64 + wid * 16 + 2 * (lane >> 2) + (size_t)(2 * (lane & 3)) * HD;
#pragma unroll
    for (int k = 0; k < 40; k++) {
      const __nv_bfloat16* b = base + (size_t)(16 * k) * HD;
      uint32_t w0 = __ldg((const uint32_t*)(b));
      uint32_t w1 = __ldg((const uint32_t*)(b + HD));
      uint32_t w8 = __ldg((const uint32_t*)(b + 8 * HD));
      uint32_t w9 = __ldg((const uint32_t*)(b + 9 * HD));
      A[k][0] = __byte_perm(w0, w1, 0x5410);
      A[k][1] = __byte_perm(w0, w1, 0x7632);
      A[k][2] = __byte_perm(w8, w9, 0x5410);
      A[k][3] = __byte_perm(w8, w9, 0x7632);
    }
  }
  const int tid128 = wid * 32 + lane;
  const bool elected = (tid128 == 0);
  const int wgbar = IS_K ? 2 : 1;
  const uint32_t bars = sb + OFF_BAR;
  const uint32_t tile = sb + (IS_K ? OFF_KT + 1024 : OFF_QX);
  const uint32_t chunk = 2 * wid + (lane >> 4), inoff = 4 * ((lane >> 2) & 3);
  const int i4 = lane & 3;

  const uint32_t xlo = desc_lo(sb + OFF_X, 16);
  auto bulk = [&](int s) {
    float acc[16];
    static_for<0, 10>([&](auto cc) {
      constexpr int c = decltype(cc)::value;
      if constexpr (!(SKIP_BULK & 4)) mbar_wait(bars + 8 * (B_XFULL + c % XST), (c / XST) & 1);
      wg_fence();
      if constexpr (!(SKIP_BULK & 1))
      static_for<0, 4>([&](auto kc) {
        constexpr int kk = decltype(kc)::value;
        wgmma_rs_n32<(c % XST) * 4096 + kk * 32, (c + kk > 0)>(acc, A[4 * c + kk][0], A[4 * c + kk][1], A[4 * c + kk][2], A[4 * c + kk][3], xlo);
      });
      wg_commit();
      if constexpr (c > 0) {
        wg_wait<1>();
        if (lane == 0) mbar_arrive(bars + 8 * (B_XEMPTY + (c - 1) % XST));
      }
    });
    wg_wait<0>();
    if (lane == 0) mbar_arrive(bars + 8 * (B_XEMPTY + 9 % XST));
    if (elected && s > 0) {
      bulk_wait0();
      red_relaxed_add(&g_segflag[s - 1], 1);
    }
    bar_sync(wgbar, 128);
#pragma unroll
    for (int t = 0; t < 4; t++) {
      int r0 = 8 * t + 2 * i4, r1 = r0 + 1;
      uint32_t w0 = pack_bf16(acc[4 * t + 0], acc[4 * t + 2]);
      uint32_t w1 = pack_bf16(acc[4 * t + 1], acc[4 * t + 3]);
      asm volatile("st.shared.u32 [%0], %1;" ::"r"(tile + r0 * 128 + ((chunk ^ (r0 & 7)) << 4) + inoff), "r"(w0) : "memory");
      asm volatile("st.shared.u32 [%0], %1;" ::"r"(tile + r1 * 128 + ((chunk ^ (r1 & 7)) << 4) + inoff), "r"(w1) : "memory");
    }
    fence_proxy_async();
    if (!IS_K) {
      bar_sync(wgbar, 128);
      if (elected) {
        if constexpr (!(SKIP_BULK & 8)) tma_store_2d(&p.tm_q, tile, h * DH + j * 64, s * SEG);
        bulk_commit();
      }
    }
  };

  const uint32_t memaddr = sb + OFF_MEM + lane * 16;
  for (int s = 0; s < NSEG; s++) {
    bulk(s);
    if (!IS_K) TSW(s == 21 && lane == 0 && wid == 0, 3);
    if (!IS_K && s + 1 == NSEG) break;
    {
      mbar_wait(bars + 8 * B_MEM, s & 1);
      if (!IS_K) TS(0);
      if (!IS_K) TSW(s == 0 && lane == 0 && wid == 0, 22);
      if (!IS_K) TSW(s == 1 && lane == 0 && wid == 0, 23);
      {
        float c0[4] = {0, 0, 0, 0}, c1[4] = {0, 0, 0, 0}, c2[4] = {0, 0, 0, 0}, c3[4] = {0, 0, 0, 0};
#pragma unroll
        for (int k = 0; k < 40; k += 4) {
          uint32_t b[4], b2[4];
          ldsm_x4_t(b, memaddr + k * 256);
          ldsm_x4_t(b2, memaddr + k * 256 + 512);
          mma16816(c0, A[k][0], A[k][1], A[k][2], A[k][3], b[0], b[1]);
          mma16816(c1, A[k + 1][0], A[k + 1][1], A[k + 1][2], A[k + 1][3], b[2], b[3]);
          mma16816(c2, A[k + 2][0], A[k + 2][1], A[k + 2][2], A[k + 2][3], b2[0], b2[1]);
          mma16816(c3, A[k + 3][0], A[k + 3][1], A[k + 3][2], A[k + 3][3], b2[2], b2[3]);
        }
#pragma unroll
        for (int i = 0; i < 4; i++) c0[i] = (c0[i] + c1[i]) + (c2[i] + c3[i]);
        uint32_t mt = sb + (IS_K ? OFF_KT : OFF_QM);
        int r0 = 2 * i4, r1 = r0 + 1;
        asm volatile("st.shared.u32 [%0], %1;" ::"r"(mt + r0 * 128 + ((chunk ^ r0) << 4) + inoff), "r"(pack_bf16(c0[0], c0[2])) : "memory");
        asm volatile("st.shared.u32 [%0], %1;" ::"r"(mt + r1 * 128 + ((chunk ^ r1) << 4) + inoff), "r"(pack_bf16(c0[1], c0[3])) : "memory");
        if (IS_K) fence_proxy_async();
      }
      if (!IS_K) TS(1);
      if (s + 1 < NSEG) {
        bar_sync(3, 256);
        if (IS_K && elected) {
          if constexpr (!(SKIP_BULK & 8)) tma_store_2d(&p.tm_k, sb + OFF_KT, h * DH + j * 64, s * 40);
          bulk_commit();
        }
        int t = IS_K ? 4 : wid;
        if (!IS_K || wid == 0) {
          uint32_t a[4], a2[4], b[4], b2[4];
          int row = lane & 7, ch = lane >> 3;
          ldsm_x4(a, sb + OFF_QM + row * 128 + ((ch ^ row) << 4));
          ldsm_x4(b, sb + OFF_KT + (8 * t + row) * 128 + ((ch ^ row) << 4));
          ldsm_x4(a2, sb + OFF_QM + row * 128 + (((ch + 4) ^ row) << 4));
          ldsm_x4(b2, sb + OFF_KT + (8 * t + row) * 128 + (((ch + 4) ^ row) << 4));
          float s0[4] = {0, 0, 0, 0}, s1[4] = {0, 0, 0, 0};
          mma16816(s0, a[0], 0, a[1], 0, b[0], b[1]);
          mma16816(s1, a2[0], 0, a2[1], 0, b2[0], b2[1]);
          mma16816(s0, a[2], 0, a[3], 0, b[2], b[3]);
          mma16816(s1, a2[2], 0, a2[3], 0, b2[2], b2[3]);
          uint32_t x0 = __float_as_uint(s0[0] + s1[0]), x1 = __float_as_uint(s0[1] + s1[1]);
          uint32_t dst = sb + OFF_SM + ((j * 5 + t) * 32 + lane) * 8;
#pragma unroll
          for (int r = 0; r < 3; r++) st_async_v2(mapa(dst, r), x0, x1, mapa(bars + 8 * B_SM, r));
        }
        if (!IS_K) TS(2);
        bar_arrive(6, 384);
        if (IS_K && wid == 1) {
          if (lane == 0) mbar_arrive_expect_tx(bars + 8 * B_SM, 3840);
          mbar_wait(bars + 8 * B_SM, s & 1);
          TSW(s == 20 && lane == 0, 5);
          const float sc = 0.07216878364870322f * 1.4426950408889634f;
          const uint32_t a = sb + OFF_SM + lane * 8;
          float sv[10];
#pragma unroll
          for (int t = 0; t < 5; t++) {
            float x0, y0, x1, y1, x2, y2;
            lds_v2(x0, y0, a + t * 256);
            lds_v2(x1, y1, a + (5 + t) * 256);
            lds_v2(x2, y2, a + (10 + t) * 256);
            sv[2 * t] = x0 + x1 + x2;
            sv[2 * t + 1] = y0 + y1 + y2;
          }
          float m = fmaxf(fmaxf(fmaxf(sv[0], sv[1]), fmaxf(sv[2], sv[3])), fmaxf(fmaxf(sv[4], sv[5]), fmaxf(sv[6], sv[7])));
          m = fmaxf(m, fmaxf(sv[8], sv[9]));
          m = fmaxf(m, __shfl_xor_sync(0xffffffffu, m, 1));
          m = fmaxf(m, __shfl_xor_sync(0xffffffffu, m, 2));
          const float ms = -m * sc;
#pragma unroll
          for (int i = 0; i < 10; i++) sv[i] = ex2f(fmaf(sv[i], sc, ms));
          float sum = ((sv[0] + sv[1]) + (sv[2] + sv[3])) + ((sv[4] + sv[5]) + (sv[6] + sv[7])) + (sv[8] + sv[9]);
          sum += __shfl_xor_sync(0xffffffffu, sum, 1);
          sum += __shfl_xor_sync(0xffffffffu, sum, 2);
          const float inv = rcpf(sum);
#pragma unroll
          for (int t = 0; t < 5; t++) sts_u32(sb + OFF_P + t * 128 + lane * 4, pack_bf16(sv[2 * t] * inv, sv[2 * t + 1] * inv));
          bar_arrive(9, 160);
          TSW(s == 20 && lane == 0, 15);
        }
        if (!IS_K && j == 0) {
          if (elected) mbar_arrive_expect_tx(bars + 8 * B_T9, 6144);
          mbar_wait(bars + 8 * B_T9, s & 1);
          float4 a, b, c;
          lds_v4(a, sb + OFF_T9 + tid128 * 16);
          lds_v4(b, sb + OFF_T9 + 2048 + tid128 * 16);
          lds_v4(c, sb + OFF_T9 + 4096 + tid128 * 16);
          char* h1 = (char*)g_xch + (s % NSLOT) * H1_SLOT + (h * NUNIT + 72) * 128 + wid * 256 + lane * 4;
          st_rlx_u32(h1, enc_neg(pack_bf16(a.x + b.x + c.x, a.y + b.y + c.y)));
          st_rlx_u32(h1 + 128, enc_neg(pack_bf16(a.z + b.z + c.z, a.w + b.w + c.w)));
        }
        bar_sync(7, 384);
      } else {
        bar_sync(wgbar, 128);
        if (elected) {
          if constexpr (!(SKIP_BULK & 8)) tma_store_2d(&p.tm_k, sb + OFF_KT, h * DH + j * 64, s * 40);
          bulk_commit();
        }
      }
    }
  }
  if (elected) {
    bulk_wait0();
    red_relaxed_add(&g_segflag[NSEG - 1], 1);
  }
}

DEVINL void publish_tile(char* h1, int tile, const float (&w)[4]) {
  st_rlx_u32(h1 + tile * 1024, enc_neg(pack_bf16(w[0], w[1])));
  st_rlx_u32(h1 + tile * 1024 + 128, enc_neg(pack_bf16(w[2], w[3])));
}
template <int T>
DEVINL void wo_issue_full(float (&w)[4], uint32_t wolo, uint32_t omlo) {
  static_for<0, 12>([&](auto kc) {
    constexpr int kk = decltype(kc)::value;
    wgmma_ss_n8_tA<T * 24576 + kk * 2048, kk * 256, 0, (kk > 0)>(w, wolo, omlo);
  });
  wg_commit();
}

DEVINL void v_wg(const MainParams& p, uint32_t sb, int h, int j, int wid, int lane) {
  const int tid128 = wid * 32 + lane;
  const bool elected = (tid128 == 0);
  const uint32_t bars = sb + OFF_BAR;
  const int i4 = lane & 3, g8 = lane >> 2;
  const uint32_t vrow = sb + OFF_VT + (wid * 16 + g8) * 80 + 4 * i4;
  const uint32_t xlo = desc_lo(sb + OFF_X, 16), wvlo = desc_lo(sb + OFF_WV, 16), memlo = desc_lo(sb + OFF_MEM, 128);
  char* const h1base = (char*)g_xch + h * NUNIT * 128 + wid * 256 + lane * 4;

  mbar_wait(bars + 8 * B_W, 0);

  for (int s = 0; s < NSEG; s++) {
    {
      float acc[16];
      static_for<0, 10>([&](auto cc) {
        constexpr int c = decltype(cc)::value;
        if constexpr (!(SKIP_BULK & 4)) mbar_wait(bars + 8 * (B_XFULL + c % XST), (c / XST) & 1);
        wg_fence();
        if constexpr (!(SKIP_BULK & 2))
        static_for<0, 4>([&](auto kc) {
          constexpr int kk = decltype(kc)::value;
          wgmma_ss_n32_tA<(4 * c + kk) * 2048, (c % XST) * 4096 + kk * 32, (c + kk > 0)>(acc, wvlo, xlo);
        });
        wg_commit();
        if constexpr (c > 0) {
          wg_wait<1>();
          if (lane == 0) mbar_arrive(bars + 8 * (B_XEMPTY + (c - 1) % XST));
        }
      });
      wg_wait<0>();
      if (lane == 0) mbar_arrive(bars + 8 * (B_XEMPTY + 9 % XST));
      if (elected && s > 0) {
        bulk_wait0();
        red_relaxed_add(&g_segflag[s - 1], 1);
      }
      bar_sync(4, 128);
#pragma unroll
      for (int t = 0; t < 4; t++) {
        sts_u32(vrow + 16 + 16 * t, pack_bf16(acc[4 * t + 0], acc[4 * t + 1]));
        sts_u32(vrow + 8 * 80 + 16 + 16 * t, pack_bf16(acc[4 * t + 2], acc[4 * t + 3]));
      }
    }
    TSW(s == 21 && lane == 0 && wid == 0, 10);
    mbar_wait(bars + 8 * B_MEM, s & 1);
    if (s + 1 < NSEG) bar_sync(6, 384);
    {
      float acc[4];
      wg_fence();
      static_for<0, 40>([&](auto kc) {
        constexpr int k = decltype(kc)::value;
        wgmma_ss_n8_tA<k * 2048, k * 256, 1, (k > 0)>(acc, wvlo, memlo);
      });
      wg_commit();
      if (elected && s + 1 < NSEG) {
        mbar_arrive_expect_tx(bars + 8 * B_OM, 2048);
      }
      wg_wait<0>();
      sts_u32(vrow, pack_bf16(acc[0], acc[1]));
      sts_u32(vrow + 8 * 80, pack_bf16(acc[2], acc[3]));
      TS(4);
      if (s + 1 == NSEG) {
        fence_proxy_async();
        bar_sync(4, 128);
        if (elected) { if constexpr (!(SKIP_BULK & 8)) tma_store_2d(&p.tm_v, sb + OFF_VT, 0, (s * NH + h) * DH + j * 64); bulk_commit(); }
        break;
      }
      __syncwarp();
      uint32_t vb0[4], vb1[4], vb2, vb3, P[5];
      {
        uint32_t base = sb + OFF_VT + (wid * 16 + (lane & 7)) * 80 + (lane >> 3) * 16;
        ldsm_x4(vb0, base);
        ldsm_x4(vb1, base + 8 * 80);
        uint32_t b2 = sb + OFF_VT + (wid * 16 + (lane & 7) + ((lane >> 3) & 1) * 8) * 80 + 64;
        ldsm_x2(vb2, vb3, b2);
      }
      bar_sync(9, 160);
#pragma unroll
      for (int t = 0; t < 5; t++) asm volatile("ld.shared.u32 %0, [%1];" : "=r"(P[t]) : "r"(sb + OFF_P + t * 128 + lane * 4) : "memory");
      float o0[4] = {0, 0, 0, 0}, o1[4] = {0, 0, 0, 0}, o2[4] = {0, 0, 0, 0}, o3[4] = {0, 0, 0, 0};
      mma16816(o0, P[0], 0, P[1], 0, vb0[0], vb0[1]);
      mma16816(o1, P[0], 0, P[1], 0, vb1[0], vb1[1]);
      mma16816(o2, P[2], 0, P[3], 0, vb0[2], vb0[3]);
      mma16816(o3, P[2], 0, P[3], 0, vb1[2], vb1[3]);
      mma1688(o0, P[4], 0, vb2);
      mma1688(o1, P[4], 0, vb3);
      uint32_t wa = pack_bf16(o0[0] + o2[0], o0[1] + o2[1]), wb = pack_bf16(o1[0] + o3[0], o1[1] + o3[1]);
      const bool odd = lane & 1, up = lane & 2;
      uint32_t rcv = __shfl_xor_sync(0xffffffffu, odd ? wa : wb, 1);
      uint32_t p0 = odd ? rcv : wa, p1 = odd ? wb : rcv;
      uint32_t q0 = __shfl_xor_sync(0xffffffffu, p0, 2), q1 = __shfl_xor_sync(0xffffffffu, p1, 2);
      uint32_t r0 = up ? q0 : p0, r1 = up ? q1 : p1, r2 = up ? p0 : q0, r3 = up ? p1 : q1;
      const uint32_t oa = (sb & 0x00FFFFFFu) + OFF_OM + (8 * j + 2 * wid + (lane & 1)) * 128 + g8 * 16;
      const int peer = up ? (j == 2 ? 1 : 2) : (j == 0 ? 1 : 0);
      st_async_v4(oa + (peer << 24), r0, r1, r2, r3, (sb & 0x00FFFFFFu) + OFF_BAR + 8 * B_OM + (peer << 24));
      if (!up) asm volatile("st.shared.v4.u32 [%0], {%1,%2,%3,%4};" ::"r"(oa + (sb & 0xFF000000u)), "r"(r0), "r"(r1), "r"(r2), "r"(r3) : "memory");
    }
    fence_proxy_async();
    bar_sync(4, 128);
    TS(6);
    {
      char* h1 = h1base + (s % NSLOT) * H1_SLOT;
      const uint32_t wolo = desc_lo(sb + OFF_WO, 16), omlo = desc_lo(sb + OFF_OM, 128);
      float w9[4], w0[4], w1[4], w2[4];
      const uint32_t om_own = omlo + j * (1024 >> 4);
      wg_fence();
      wgmma_ss_n8_tA<73728 + 0 * 2048, 0 * 256, 0, 0>(w9, wolo, om_own);
      wgmma_ss_n8_tA<73728 + 1 * 2048, 1 * 256, 0, 1>(w9, wolo, om_own);
      wgmma_ss_n8_tA<73728 + 2 * 2048, 2 * 256, 0, 1>(w9, wolo, om_own);
      wgmma_ss_n8_tA<73728 + 3 * 2048, 3 * 256, 0, 1>(w9, wolo, om_own);
      wg_commit();
      mbar_wait(bars + 8 * B_OM, s & 1);
      fence_proxy_async();
      TS(8);
      wg_fence();
      wo_issue_full<0>(w0, wolo, omlo);
      wg_wait<1>();
      st_async_v4((sb & 0x00FFFFFFu) + OFF_T9 + j * 2048 + tid128 * 16, __float_as_uint(w9[0]), __float_as_uint(w9[1]),
                    __float_as_uint(w9[2]), __float_as_uint(w9[3]), (sb & 0x00FFFFFFu) + OFF_BAR + 8 * B_T9);
      wo_issue_full<1>(w1, wolo, omlo);
      wg_wait<1>();
      publish_tile(h1, 3 * j + 0, w0);
      wo_issue_full<2>(w2, wolo, omlo);
      wg_wait<1>();
      publish_tile(h1, 3 * j + 1, w1);
      wg_wait<0>();
      bar_arrive(7, 384);
      TS(7);
      publish_tile(h1, 3 * j + 2, w2);
      bar_arrive(8, 128 + 96);
      TS(9);
    }
    if (elected) {
      if constexpr (!(SKIP_BULK & 8)) tma_store_2d(&p.tm_v, sb + OFF_VT, 0, (s * NH + h) * DH + j * 64);
      bulk_commit();
    }
  }
  if (elected) {
    bulk_wait0();
    red_relaxed_add(&g_segflag[NSEG - 1], 1);
  }
}

DEVINL bool nz4(const uint4& v) { return v.x != 0 && v.y != 0 && v.z != 0 && v.w != 0; }
DEVINL uint32_t clk32() { uint32_t c; asm volatile("mov.u32 %0, %clock;" : "=r"(c)); return c; }
DEVINL void spin_clk(int n) {
  uint32_t t = clk32();
  while ((int)(clk32() - t) < n) {}
}

DEVINL void comm_wg(const MainParams& p, uint32_t sb, int h, int j, int cta, int wid, int lane) {
  const uint32_t bars = sb + OFF_BAR;
  if (wid == 0) {
    if (lane == 0) {
      mbar_arrive_expect_tx(bars + 8 * B_W, 2 * 81920);
      for (int c = 0; c < 5; c++) tma_load_2d(sb + OFF_WV + c * 16384, &p.tm_wv, h * DH + j * 64, c * 128, bars + 8 * B_W);
      for (int c = 0; c < XST; c++) {
        mbar_arrive_expect_tx(bars + 8 * (B_XFULL + c), 4096);
        tma_load_2d(sb + OFF_X + c * 4096, &p.tm_x, c * 64, 0, bars + 8 * (B_XFULL + c));
      }
      for (int t = 0; t < 3; t++)
        for (int c = 0; c < 3; c++)
          tma_load_2d(sb + OFF_WO + t * 24576 + c * 8192, &p.tm_wo, (3 * j + t) * 64, h * DH + c * 64, bars + 8 * B_W);
      tma_load_2d(sb + OFF_WO + 73728, &p.tm_wo, 9 * 64, h * DH + j * 64, bars + 8 * B_W);
      uint32_t par = 0;
      for (int sg = 0; sg < ((SKIP_BULK & 4) ? 0 : NSEG); sg++) {
        if (cta < 10 && sg + 2 < NSEG) tma_prefetch_2d(&p.tm_x, cta * 64, (sg + 2) * SEG);
#pragma unroll 1
        for (int half = (sg == 0 ? 1 : 0); half < 2; half++) {
#pragma unroll 1
          for (int st = 0; st < XST; st++) {
            mbar_wait(bars + 8 * (B_XEMPTY + st), par);
            mbar_arrive_expect_tx(bars + 8 * (B_XFULL + st), 4096);
            tma_load_2d(sb + OFF_X + st * 4096, &p.tm_x, (half * XST + st) * 64, sg * SEG, bars + 8 * (B_XFULL + st));
          }
          par ^= 1;
        }
      }
    }
    return;
  }
  const int pt = (wid - 1) * 32 + lane;
  for (int d = pt; d < DM; d += 96) {
    uint32_t w[4];
#pragma unroll
    for (int r = 0; r < 4; r++) {
      uint32_t lo = __bfloat16_as_ushort(p.mem0[(2 * r) * DM + d]), hi = __bfloat16_as_ushort(p.mem0[(2 * r + 1) * DM + d]);
      w[r] = lo | (hi << 16);
    }
    asm volatile("st.shared.v4.u32 [%0], {%1,%2,%3,%4};" ::"r"(sb + OFF_MEM + d * 16), "r"(w[0]), "r"(w[1]), "r"(w[2]), "r"(w[3]) : "memory");
  }
  fence_proxy_async();
  __syncwarp();
  if (lane == 0) mbar_arrive(bars + 8 * B_MEM);

  const bool is_red = (wid <= 2) && (cta < NUNIT);
  const int dly2 = is_red ? p.d2 : p.d3;
  char* const xb = (char*)g_xch;
  uint32_t ptv = pt;
#pragma unroll 1
  for (int x = 0; x + 1 < NSEG; x++) {
    const uint32_t slot = x % NSLOT;
    mbar_wait(bars + 8 * B_MEM, x & 1);
    asm volatile("" : "+r"(ptv));
    const uint32_t col16 = (((ptv >> 5) & 1) * 4 + ((ptv >> 2) & 3)) * 16;
    const uint32_t off_src = ((4 * ((ptv >> 4) & 1) + (ptv & 3)) * NUNIT + cta) * 128 + col16;
    bar_sync(8, 128 + 96);
    if (is_red) {
      const char* src = xb + slot * H1_SLOT + off_src;
      spin_clk(p.d1);
      uint4 v[4];
#pragma unroll
      for (int c = 0; c < 4; c++) v[c] = ld_rlx_v4(src + c * 8 * NUNIT * 128);
      uint32_t n = 0;
      while (!__all_sync(0xffffffffu, nz4(v[0]) && nz4(v[1]) && nz4(v[2]) && nz4(v[3]))) {
#pragma unroll
        for (int c = 0; c < 4; c++)
          if (!nz4(v[c])) v[c] = ld_rlx_v4(src + c * 8 * NUNIT * 128);
        if (++n > (1u << 22)) __trap();
      }
      TSW(x == 20 && ptv == 0, 11);
      DBGADD((ptv & 31) == 0, 16, n);
      float f[8];
      f[0] = __uint_as_float(v[0].x << 16); f[1] = __uint_as_float(v[0].x & 0xffff0000u);
      f[2] = __uint_as_float(v[0].y << 16); f[3] = __uint_as_float(v[0].y & 0xffff0000u);
      f[4] = __uint_as_float(v[0].z << 16); f[5] = __uint_as_float(v[0].z & 0xffff0000u);
      f[6] = __uint_as_float(v[0].w << 16); f[7] = __uint_as_float(v[0].w & 0xffff0000u);
#pragma unroll
      for (int c = 1; c < 4; c++) {
        f[0] += __uint_as_float(v[c].x << 16); f[1] += __uint_as_float(v[c].x & 0xffff0000u);
        f[2] += __uint_as_float(v[c].y << 16); f[3] += __uint_as_float(v[c].y & 0xffff0000u);
        f[4] += __uint_as_float(v[c].z << 16); f[5] += __uint_as_float(v[c].z & 0xffff0000u);
        f[6] += __uint_as_float(v[c].w << 16); f[7] += __uint_as_float(v[c].w & 0xffff0000u);
      }
      const bool b0 = ptv & 1, b1 = ptv & 2;
      float e[4], e2[2];
#pragma unroll
      for (int q = 0; q < 4; q++) {
        float snd = b0 ? f[q] : f[q + 4], kp = b0 ? f[q + 4] : f[q];
        e[q] = kp + __shfl_xor_sync(0xffffffffu, snd, 1);
      }
#pragma unroll
      for (int q = 0; q < 2; q++) {
        float snd = b1 ? e[q] : e[q + 2], kp = b1 ? e[q + 2] : e[q];
        e2[q] = kp + __shfl_xor_sync(0xffffffffu, snd, 2);
      }
      e2[0] += __shfl_xor_sync(0xffffffffu, e2[0], 16);
      e2[1] += __shfl_xor_sync(0xffffffffu, e2[1], 16);
      uint32_t w = pack_bf16(e2[0], e2[1]);
      w = w ? w : 0x80008000u;
      const uint32_t off_dst = H2_BASE + ((4 * ((ptv >> 4) & 1)) * NUNIT + cta) * 128 + col16 + (((ptv & 1) << 1) | ((ptv >> 1) & 1)) * 4;
      char* dst = xb + slot * H2_SLOT + off_dst;
      st_rlx_u32(dst, w);
      st_rlx_u32(dst + NUNIT * 128, w);
      st_rlx_u32(dst + 2 * NUNIT * 128, w);
      st_rlx_u32(dst + 3 * NUNIT * 128, w);
      TSW(x == 20 && ptv == 0, 12);
#pragma unroll
      for (int c = 0; c < 4; c++) st_rlx_v4((void*)(src + c * 8 * NUNIT * 128), 0, 0, 0, 0);
    }
    spin_clk(dly2);
    {
      asm volatile("" : "+r"(ptv));
      const uint32_t off_poll = H2_BASE + (h % NREP) * NUNIT * 128 + ptv * 16;
      const char* src = xb + slot * H2_SLOT + off_poll;
      const bool act7 = ptv < DM - 6 * 96;
      uint4 v[7];
#pragma unroll
      for (int k = 0; k < 6; k++) v[k] = ld_rlx_v4(src + k * 96 * 16);
      v[6] = act7 ? ld_rlx_v4(src + 6 * 96 * 16) : make_uint4(1, 1, 1, 1);
      uint32_t n = 0;
      while (true) {
        bool ok = true;
#pragma unroll
        for (int k = 0; k < 7; k++) ok = ok && nz4(v[k]);
        if (__all_sync(0xffffffffu, ok)) break;
#pragma unroll
        for (int k = 0; k < 7; k++)
          if (!nz4(v[k])) v[k] = ld_rlx_v4(src + k * 96 * 16);
        if (++n > (1u << 22)) __trap();
      }
      TSW(x == 20 && ptv == 32, 13);
      DBGADD((ptv & 31) == 0, 17, n);
      const uint32_t mem_dst = sb + OFF_MEM + ptv * 16;
#pragma unroll
      for (int k = 0; k < 7; k++)
        if (k < 6 || act7)
          asm volatile("st.shared.v4.u32 [%0], {%1,%2,%3,%4};" ::"r"(mem_dst + k * 96 * 16), "r"(v[k].x ^ 0x80008000u), "r"(v[k].y ^ 0x80008000u),
                       "r"(v[k].z ^ 0x80008000u), "r"(v[k].w ^ 0x80008000u) : "memory");
      fence_proxy_async();
      __syncwarp();
      if ((ptv & 31) == 0) mbar_arrive(bars + 8 * B_MEM);
      if (x >= 1 && h < NREP && j == 0) {
        char* old = xb + ((x - 1) % NSLOT) * H2_SLOT + H2_BASE + (h % NREP) * NUNIT * 128 + ptv * 16;
#pragma unroll
        for (int k = 0; k < 6; k++) st_rlx_v4(old + k * 96 * 16, 0, 0, 0, 0);
        if (act7) st_rlx_v4(old + 6 * 96 * 16, 0, 0, 0, 0);
      }
    }
  }
}

__global__ void __cluster_dims__(3, 1, 1) __launch_bounds__(512, 1) main_kernel(const __grid_constant__ MainParams p) {
  extern __shared__ __align__(1024) uint8_t smem[];
  const uint32_t sb = smem_u32(smem);
  const int tid = threadIdx.x, wg = tid >> 7, wid = (tid >> 5) & 3, lane = tid & 31;
  const int cta = blockIdx.x, h = cta / 3, j = cta % 3;
  if (tid == 0) {
    const uint32_t bars = sb + OFF_BAR;
    for (int i = 0; i < XST; i++) {
      mbar_init(bars + 8 * (B_XFULL + i), 1);
      mbar_init(bars + 8 * (B_XEMPTY + i), 12);
    }
    mbar_init(bars + 8 * B_W, 1);
    mbar_init(bars + 8 * B_MEM, 3);
    mbar_init(bars + 8 * B_SM, 1);
    mbar_init(bars + 8 * B_OM, 1);
    mbar_init(bars + 8 * B_T9, 1);
    asm volatile("fence.mbarrier_init.release.cluster;" ::: "memory");
  }
  __syncthreads();
  cluster_sync_all();
  asm volatile("griddepcontrol.launch_dependents;" ::: "memory");
  TSW(tid == 0, 21);
  if (wg == 0) {
    asm volatile("setmaxnreg.inc.sync.aligned.u32 208;");
    proj_wg<0>(p, sb, h, j, wid, lane);
  } else if (wg == 1) {
    asm volatile("setmaxnreg.inc.sync.aligned.u32 208;");
    proj_wg<1>(p, sb, h, j, wid, lane);
  } else if (wg == 2) {
    asm volatile("setmaxnreg.dec.sync.aligned.u32 56;");
    v_wg(p, sb, h, j, wid, lane);
  } else {
    asm volatile("setmaxnreg.dec.sync.aligned.u32 40;");
    comm_wg(p, sb, h, j, cta, wid, lane);
  }
}

__device__ __nv_bfloat16 g_hid[SEQ * FF];
__device__ __nv_bfloat16 g_o[SEQ * HD];
__device__ unsigned g_ctr;
__device__ unsigned g_f1flag[16], g_f2flag[80], g_atflag[16];

struct AuxParams {
  CUtensorMap tm_bx, tm_wg, tm_wu, tm_hid, tm_wd, tm_o, tm_wo128, tm_q, tm_k, tm_v3, tm_ost;
  const __nv_bfloat16* ax;
  const __nv_bfloat16* gate_w;
  __nv_bfloat16* out;
};

constexpr int N_F1 = 16 * 12, N_F2 = 16 * 5, N_AT_TILE = 32, N_W_TILE = 5;
constexpr int N_ITEMS = N_F1 + N_F2 + 16 * (N_AT_TILE + N_W_TILE);
constexpr int AUX_STAGES = 4, AUX_STAGE_BYTES = 49152;
constexpr int AUX_OFF_BAR = AUX_STAGES * AUX_STAGE_BYTES;
constexpr int AUX_SMEM = AUX_OFF_BAR + 256;
constexpr int AT_HEAD_BYTES = 12288 + 15360 + 15360 + 1024;

template <int N>
struct WG;
#define ACC_REGS_64 "%0,%1,%2,%3,%4,%5,%6,%7,%8,%9,%10,%11,%12,%13,%14,%15,%16,%17,%18,%19,%20,%21,%22,%23,%24,%25,%26,%27,%28,%29,%30,%31," \
                    "%32,%33,%34,%35,%36,%37,%38,%39,%40,%41,%42,%43,%44,%45,%46,%47,%48,%49,%50,%51,%52,%53,%54,%55,%56,%57,%58,%59,%60,%61,%62,%63"
#define ACC8(d, o) "+f"(d[o + 0]), "+f"(d[o + 1]), "+f"(d[o + 2]), "+f"(d[o + 3]), "+f"(d[o + 4]), "+f"(d[o + 5]), "+f"(d[o + 6]), "+f"(d[o + 7])
#define ACC64(d, o) ACC8(d, o), ACC8(d, o + 8), ACC8(d, o + 16), ACC8(d, o + 24), ACC8(d, o + 32), ACC8(d, o + 40), ACC8(d, o + 48), ACC8(d, o + 56)
DEVINL void wgmma_n128_tB(float* d, uint64_t da, uint64_t db, int scale_d) {
  asm volatile(
      "{\n.reg .pred p;\nsetp.ne.u32 p, %66, 0;\n"
      "wgmma.mma_async.sync.aligned.m64n128k16.f32.bf16.bf16 {" ACC_REGS_64 "}, %64, %65, p, 1, 1, 0, 1;\n}"
      : ACC64(d, 0)
      : "l"(da), "l"(db), "r"(scale_d));
}

DEVINL float bf16r(float x) { return __bfloat162float(__float2bfloat16_rn(x)); }
DEVINL float sigmoidf_(float x) { return 1.0f / (1.0f + __expf(-x)); }

DEVINL void wait_flag(const unsigned* f, unsigned target) {
  uint32_t n = 0;
  while (ld_acq_u32(f) < target) {
    __nanosleep(100);
    if (++n > (1u << 24)) __trap();
  }
}

DEVINL float gate_rows(const __nv_bfloat16* ax, const __nv_bfloat16* gw, int row0, int lane) {
  float res = 0.f;
  for (int r = 0; r < 16; r++) {
    const uint32_t* xr = (const uint32_t*)(ax + (size_t)(row0 + r) * DM);
    const uint32_t* wr = (const uint32_t*)gw;
    float s = 0.f;
#pragma unroll
    for (int i = 0; i < 10; i++) {
      uint32_t a = __ldg(xr + lane + 32 * i), b = __ldg(wr + lane + 32 * i);
      s += bf16r(__uint_as_float(a << 16) * __uint_as_float(b << 16));
      s += bf16r(__uint_as_float(a & 0xffff0000u) * __uint_as_float(b & 0xffff0000u));
    }
#pragma unroll
    for (int o = 16; o > 0; o >>= 1) s += __shfl_xor_sync(0xffffffffu, s, o);
    if (lane == r) res = bf16r(sigmoidf_(bf16r(s)));
  }
  return res;
}

__global__ void __launch_bounds__(384, 1) aux_kernel(const __grid_constant__ AuxParams p) {
  extern __shared__ __align__(1024) uint8_t smem[];
  const uint32_t sb = smem_u32(smem);
  const int tid = threadIdx.x, wg = tid >> 7, wid = (tid >> 5) & 3, lane = tid & 31;
  const uint32_t bars = sb + AUX_OFF_BAR;
  volatile int* s_item = (volatile int*)(smem + AUX_OFF_BAR + 128);
  if (tid == 0) {
    for (int i = 0; i < AUX_STAGES; i++) { mbar_init(bars + 8 * i, 1); mbar_init(bars + 8 * (AUX_STAGES + i), 8); }
    mbar_init(bars + 8 * (2 * AUX_STAGES), 1);
    asm volatile("fence.mbarrier_init.release.cluster;" ::: "memory");
  }
  __syncthreads();
  uint32_t it = 0;
  uint32_t at_phase = 0;
  while (true) {
    if (tid == 128) *s_item = (int)atomicAdd(&g_ctr, 1u);
    __syncthreads();
    const int item = *s_item;
    __syncthreads();
    if (item >= N_ITEMS) break;
    int type, tt, nn, seg = 0;
    if (item < N_F1) { type = 0; tt = item / 12; nn = item % 12; }
    else if (item < N_F1 + N_F2) { type = 1; tt = (item - N_F1) / 5; nn = (item - N_F1) % 5; }
    else {
      int r = item - N_F1 - N_F2;
      tt = r / (N_AT_TILE + N_W_TILE);
      int q = r % (N_AT_TILE + N_W_TILE);
      if (q < N_AT_TILE) { type = 2; seg = tt * 4 + q / 8; nn = q % 8; }
      else { type = 3; nn = q - N_AT_TILE; }
    }
    if (type != 2) {
      const int nk = (type == 0) ? 10 : (type == 1 ? 24 : 96);
      if (wg == 0) {
        if (tid == 0) {
          if (type == 1) wait_flag(&g_f1flag[tt], 12);
          if (type == 3) { wait_flag(&g_atflag[tt], N_AT_TILE); }
          fence_proxy_async_all();
          for (int k = 0; k < nk; k++, it++) {
            const uint32_t st = it % AUX_STAGES, ph = (it / AUX_STAGES) & 1;
            mbar_wait(bars + 8 * (AUX_STAGES + st), ph ^ 1);
            const uint32_t a = sb + st * AUX_STAGE_BYTES, b = a + 16384, fb = bars + 8 * st;
            if (type == 0) {
              mbar_arrive_expect_tx(fb, 49152);
              tma_load_2d(a, &p.tm_bx, k * 64, tt * 128, fb);
              tma_load_2d(b, &p.tm_wg, nn * 128, k * 64, fb);
              tma_load_2d(b + 8192, &p.tm_wg, nn * 128 + 64, k * 64, fb);
              tma_load_2d(b + 16384, &p.tm_wu, nn * 128, k * 64, fb);
              tma_load_2d(b + 24576, &p.tm_wu, nn * 128 + 64, k * 64, fb);
            } else {
              mbar_arrive_expect_tx(fb, 32768);
              tma_load_2d(a, type == 1 ? &p.tm_hid : &p.tm_o, k * 64, tt * 128, fb);
              const CUtensorMap* tb = type == 1 ? &p.tm_wd : &p.tm_wo128;
              tma_load_2d(b, tb, nn * 128, k * 64, fb);
              tma_load_2d(b + 8192, tb, nn * 128 + 64, k * 64, fb);
            }
          }
        } else {
          it += nk;
        }
        it = __shfl_sync(0xffffffffu, it, 0);
        if (wid != 0) it += 0;
      } else {
        const int cw = wg - 1;
        float acc[128];
        const int row_l = cw * 64 + wid * 16 + (lane >> 2);
        for (int k = 0; k < nk; k++, it++) {
          const uint32_t st = it % AUX_STAGES, ph = (it / AUX_STAGES) & 1;
          mbar_wait(bars + 8 * st, ph);
          const uint32_t a = sb + st * AUX_STAGE_BYTES + cw * 8192, b = sb + st * AUX_STAGE_BYTES + 16384;
          wg_fence();
#pragma unroll
          for (int kk = 0; kk < 4; kk++) {
            uint64_t da = make_desc(a + kk * 32, 16, 1024, 1);
            wgmma_n128_tB(acc, da, make_desc(b + kk * 2048, 8192, 1024, 1), (k | kk) != 0);
            if (type == 0) wgmma_n128_tB(acc + 64, da, make_desc(b + 16384 + kk * 2048, 8192, 1024, 1), (k | kk) != 0);
          }
          wg_commit();
          wg_wait<0>();
          if (lane == 0) mbar_arrive(bars + 8 * (AUX_STAGES + st));
        }
        const int grow = tt * 128 + row_l;
        if (type == 0) {
          __nv_bfloat16* dst = g_hid + (size_t)grow * FF + nn * 128 + 2 * (lane & 3);
#pragma unroll
          for (int t = 0; t < 16; t++) {
            float h00 = bf16r(sigmoidf_(bf16r(acc[4 * t + 0]))) * bf16r(acc[64 + 4 * t + 0]);
            float h01 = bf16r(sigmoidf_(bf16r(acc[4 * t + 1]))) * bf16r(acc[64 + 4 * t + 1]);
            float h10 = bf16r(sigmoidf_(bf16r(acc[4 * t + 2]))) * bf16r(acc[64 + 4 * t + 2]);
            float h11 = bf16r(sigmoidf_(bf16r(acc[4 * t + 3]))) * bf16r(acc[64 + 4 * t + 3]);
            *(uint32_t*)(dst + 8 * t) = pack_bf16(h00, h01);
            *(uint32_t*)(dst + 8 * FF + 8 * t) = pack_bf16(h10, h11);
          }
          __threadfence();
          bar_sync(1, 256);
          if (tid == 128) red_release_add(&g_f1flag[tt], 1);
        } else {
          float gl = gate_rows(p.ax, p.gate_w, tt * 128 + cw * 64 + wid * 16, lane);
          const float g0 = __shfl_sync(0xffffffffu, gl, lane >> 2), g1 = __shfl_sync(0xffffffffu, gl, 8 + (lane >> 2));
          __nv_bfloat16* dst = p.out + (size_t)grow * DM + nn * 128 + 2 * (lane & 3);
          if (type == 1) {
            const float m0 = bf16r(1.0f - g0), m1 = bf16r(1.0f - g1);
#pragma unroll
            for (int t = 0; t < 16; t++) {
              *(uint32_t*)(dst + 8 * t) = pack_bf16(m0 * bf16r(acc[4 * t + 0]), m0 * bf16r(acc[4 * t + 1]));
              *(uint32_t*)(dst + 8 * DM + 8 * t) = pack_bf16(m1 * bf16r(acc[4 * t + 2]), m1 * bf16r(acc[4 * t + 3]));
            }
            __threadfence();
            bar_sync(1, 256);
            if (tid == 128) red_release_add(&g_f2flag[tt * 5 + nn], 1);
          } else {
            if (lane == 0) wait_flag(&g_f2flag[tt * 5 + nn], 1);
            __syncwarp();
#pragma unroll
            for (int t = 0; t < 16; t++) {
              uint32_t b0 = *(volatile uint32_t*)(dst + 8 * t), b1 = *(volatile uint32_t*)(dst + 8 * DM + 8 * t);
              float o00 = bf16r(g0 * bf16r(acc[4 * t + 0])) + __uint_as_float(b0 << 16);
              float o01 = bf16r(g0 * bf16r(acc[4 * t + 1])) + __uint_as_float(b0 & 0xffff0000u);
              float o10 = bf16r(g1 * bf16r(acc[4 * t + 2])) + __uint_as_float(b1 << 16);
              float o11 = bf16r(g1 * bf16r(acc[4 * t + 3])) + __uint_as_float(b1 & 0xffff0000u);
              *(uint32_t*)(dst + 8 * t) = pack_bf16(o00, o01);
              *(uint32_t*)(dst + 8 * DM + 8 * t) = pack_bf16(o10, o11);
            }
          }
        }
      }
    } else {
      const uint32_t fb = bars + 8 * (2 * AUX_STAGES);
      if (tid == 0) {
        wait_flag(&g_segflag[seg], 288);
        fence_proxy_async_all();
        mbar_arrive_expect_tx(fb, 4 * (12288 + 15360 + 15360));
        for (int hh = 0; hh < 4; hh++) {
          const int h = nn * 4 + hh;
          const uint32_t base = sb + hh * AT_HEAD_BYTES;
          for (int c = 0; c < 3; c++) {
            tma_load_2d(base + c * 4096, &p.tm_q, h * DH + c * 64, seg * SEG, fb);
            tma_load_2d(base + 12288 + c * 5120, &p.tm_k, h * DH + c * 64, seg * 40, fb);
          }
          tma_load_2d(base + 27648, &p.tm_v3, 0, (seg * NH + h) * DH, fb);
        }
      }
      if (wg > 0) {
        const int w8 = (wg - 1) * 4 + wid, hh = w8 >> 1, mt = w8 & 1;
        const uint32_t base = sb + hh * AT_HEAD_BYTES;
        mbar_wait(fb, at_phase);
        const int r8 = lane & 7;
        float S[5][4];
#pragma unroll
        for (int t = 0; t < 5; t++) S[t][0] = S[t][1] = S[t][2] = S[t][3] = 0.f;
#pragma unroll
        for (int c = 0; c < 3; c++) {
#pragma unroll
          for (int kk = 0; kk < 4; kk++) {
            uint32_t a[4];
            {
              int row = mt * 16 + (lane & 15), ch = 2 * kk + (lane >> 4);
              ldsm_x4(a, base + c * 4096 + row * 128 + ((ch ^ (row & 7)) << 4));
            }
#pragma unroll
            for (int t = 0; t < 5; t++) {
              uint32_t b0, b1;
              int row = 8 * t + r8, ch = 2 * kk + ((lane >> 3) & 1);
              ldsm_x2(b0, b1, base + 12288 + c * 5120 + row * 128 + ((ch ^ (row & 7)) << 4));
              mma16816(S[t], a[0], a[1], a[2], a[3], b0, b1);
            }
          }
        }
        const float sc = 0.07216878364870322f * 1.4426950408889634f;
        const int q0 = mt * 16 + (lane >> 2), q1 = q0 + 8;
        float m0 = -1e30f, m1 = -1e30f;
#pragma unroll
        for (int t = 0; t < 5; t++) {
#pragma unroll
          for (int e = 0; e < 2; e++) {
            int key = 8 * t + 2 * (lane & 3) + e - 8;
            if (key > q0) S[t][e] = -1e30f;
            if (key > q1) S[t][2 + e] = -1e30f;
            m0 = fmaxf(m0, S[t][e]);
            m1 = fmaxf(m1, S[t][2 + e]);
          }
        }
        m0 = fmaxf(m0, __shfl_xor_sync(0xffffffffu, m0, 1)); m0 = fmaxf(m0, __shfl_xor_sync(0xffffffffu, m0, 2));
        m1 = fmaxf(m1, __shfl_xor_sync(0xffffffffu, m1, 1)); m1 = fmaxf(m1, __shfl_xor_sync(0xffffffffu, m1, 2));
        float s0 = 0.f, s1 = 0.f;
#pragma unroll
        for (int t = 0; t < 5; t++) {
#pragma unroll
          for (int e = 0; e < 2; e++) {
            S[t][e] = exp2f((S[t][e] - m0) * sc); s0 += S[t][e];
            S[t][2 + e] = exp2f((S[t][2 + e] - m1) * sc); s1 += S[t][2 + e];
          }
        }
        s0 += __shfl_xor_sync(0xffffffffu, s0, 1); s0 += __shfl_xor_sync(0xffffffffu, s0, 2);
        s1 += __shfl_xor_sync(0xffffffffu, s1, 1); s1 += __shfl_xor_sync(0xffffffffu, s1, 2);
        const float i0 = 1.0f / s0, i1 = 1.0f / s1;
        uint32_t P0[5], P1[5];
#pragma unroll
        for (int t = 0; t < 5; t++) { P0[t] = pack_bf16(S[t][0] * i0, S[t][1] * i0); P1[t] = pack_bf16(S[t][2] * i1, S[t][3] * i1); }
        __syncwarp();
#pragma unroll 4
        for (int n = 0; n < 24; n++) {
          uint32_t b[4], b4;
          const uint32_t vb = base + 27648 + (8 * n + r8) * 80;
          ldsm_x4(b, vb + (lane >> 3) * 16);
          ldsm_x1(b4, vb + 64);
          float o[4] = {0, 0, 0, 0};
          mma16816(o, P0[0], P1[0], P0[1], P1[1], b[0], b[1]);
          mma16816(o, P0[2], P1[2], P0[3], P1[3], b[2], b[3]);
          mma1688(o, P0[4], P1[4], b4);
          const int c = n >> 3, ch = n & 7;
          const int ra = mt * 16 + (lane >> 2), rb = ra + 8;
          sts_u32(base + c * 4096 + ra * 128 + ((ch ^ (ra & 7)) << 4) + 4 * (lane & 3), pack_bf16(o[0], o[1]));
          sts_u32(base + c * 4096 + rb * 128 + ((ch ^ (rb & 7)) << 4) + 4 * (lane & 3), pack_bf16(o[2], o[3]));
        }
        fence_proxy_async();
        bar_sync(2 + hh, 64);
        if (mt == 0 && lane == 0) {
          const int h = nn * 4 + hh;
          for (int c = 0; c < 3; c++) tma_store_2d(&p.tm_ost, base + c * 4096, h * DH + c * 64, seg * SEG);
          bulk_commit();
          bulk_wait0();
          fence_proxy_async_all();
          __threadfence();
        }
        bar_sync(1, 256);
        if (tid == 128) red_release_add(&g_atflag[tt], 1);
      }
      at_phase ^= 1;
    }
  }
  asm volatile("griddepcontrol.wait;" ::: "memory");
}

__global__ void cleanup_kernel() {
  int i = blockIdx.x * blockDim.x + threadIdx.x, n = gridDim.x * blockDim.x;
  for (int k = i; k < (int)(NSLOT * H2_SLOT / 16); k += n) g_xch[H2_BASE / 16 + k] = make_uint4(0, 0, 0, 0);
  if (i < NSEG) g_segflag[i] = 0;
  if (i < 16) { g_f1flag[i] = 0; g_atflag[i] = 0; }
  if (i < 80) g_f2flag[i] = 0;
  if (i == 0) g_ctr = 0;
}

typedef CUresult (*PFN_encodeTiled)(CUtensorMap*, CUtensorMapDataType, cuuint32_t, void*, const cuuint64_t*, const cuuint64_t*,
                                    const cuuint32_t*, const cuuint32_t*, CUtensorMapInterleave, CUtensorMapSwizzle,
                                    CUtensorMapL2promotion, CUtensorMapFloatOOBfill);
static PFN_encodeTiled get_encode() {
  static PFN_encodeTiled fn = nullptr;
  if (!fn) {
    void* f = nullptr;
    cudaDriverEntryPointQueryResult qr;
    cudaGetDriverEntryPoint("cuTensorMapEncodeTiled", &f, cudaEnableDefault, &qr);
    fn = (PFN_encodeTiled)f;
  }
  return fn;
}
static void make_tm(CUtensorMap* tm, const void* ptr, uint64_t rows, uint64_t cols, uint64_t pitch_elems, uint32_t brows,
                    uint32_t bcols, CUtensorMapSwizzle swz) {
  cuuint64_t dims[2] = {cols, rows};
  cuuint64_t strides[1] = {pitch_elems * 2};
  cuuint32_t box[2] = {bcols, brows};
  cuuint32_t es[2] = {1, 1};
  get_encode()(tm, CU_TENSOR_MAP_DATA_TYPE_BFLOAT16, 2, (void*)ptr, dims, strides, box, es, CU_TENSOR_MAP_INTERLEAVE_NONE, swz,
               CU_TENSOR_MAP_L2_PROMOTION_L2_256B, CU_TENSOR_MAP_FLOAT_OOB_FILL_NONE);
}

#define DLY1 500
#define DLY2 500
#define DLY3 1700
extern "C" void kernel_launch(void* const* d_in, const int* in_sizes, int n_in, void* d_out, int out_size) {
  static MainParams mp;
  static AuxParams ap;
  static int n_sm = 0;
  if (n_sm == 0) {
    void *q, *k, *v, *hid, *o;
    cudaGetSymbolAddress(&q, g_q);
    cudaGetSymbolAddress(&k, g_k);
    cudaGetSymbolAddress(&v, g_vT);
    cudaGetSymbolAddress(&hid, g_hid);
    cudaGetSymbolAddress(&o, g_o);
    const CUtensorMapSwizzle S128 = CU_TENSOR_MAP_SWIZZLE_128B, S0 = CU_TENSOR_MAP_SWIZZLE_NONE;
    make_tm(&mp.tm_x, d_in[0], SEQ, DM, DM, 32, 64, S128);
    make_tm(&mp.tm_wv, d_in[4], DM, HD, HD, 128, 64, S128);
    make_tm(&mp.tm_wo, d_in[5], HD, DM, DM, 64, 64, S128);
    make_tm(&mp.tm_q, q, SEQ, HD, HD, 32, 64, S128);
    make_tm(&mp.tm_k, k, NSEG * 40, HD, HD, 40, 64, S128);
    make_tm(&mp.tm_v, v, (uint64_t)NSEG * HD, 40, 40, 64, 40, S0);
    mp.wq = (const __nv_bfloat16*)d_in[2];
    mp.wk = (const __nv_bfloat16*)d_in[3];
    mp.mem0 = (const __nv_bfloat16*)d_in[1];
    mp.d1 = DLY1; mp.d2 = DLY2; mp.d3 = DLY3; mp.skip = 0;
    make_tm(&ap.tm_bx, d_in[0], SEQ, DM, DM, 128, 64, S128);
    make_tm(&ap.tm_wg, d_in[8], DM, FF, FF, 64, 64, S128);
    make_tm(&ap.tm_wu, d_in[9], DM, FF, FF, 64, 64, S128);
    make_tm(&ap.tm_hid, hid, SEQ, FF, FF, 128, 64, S128);
    make_tm(&ap.tm_wd, d_in[10], FF, DM, DM, 64, 64, S128);
    make_tm(&ap.tm_o, o, SEQ, HD, HD, 128, 64, S128);
    make_tm(&ap.tm_wo128, d_in[5], HD, DM, DM, 64, 64, S128);
    ap.tm_q = mp.tm_q;
    ap.tm_k = mp.tm_k;
    make_tm(&ap.tm_v3, v, (uint64_t)NSEG * HD, 40, 40, 192, 40, S0);
    make_tm(&ap.tm_ost, o, SEQ, HD, HD, 32, 64, S128);
    ap.ax = (const __nv_bfloat16*)d_in[0];
    ap.gate_w = (const __nv_bfloat16*)d_in[11];
    cudaFuncSetAttribute(main_kernel, cudaFuncAttributeMaxDynamicSharedMemorySize, MAIN_SMEM);
    cudaFuncSetAttribute(aux_kernel, cudaFuncAttributeMaxDynamicSharedMemorySize, AUX_SMEM);
    cudaDeviceGetAttribute(&n_sm, cudaDevAttrMultiProcessorCount, 0);
  }
  ap.out = (__nv_bfloat16*)d_out;
  cudaStream_t st = cudaStreamPerThread;
  main_kernel<<<96, 512, MAIN_SMEM, st>>>(mp);
  {
    cudaLaunchConfig_t cfg = {};
    cfg.gridDim = dim3(n_sm);
    cfg.blockDim = dim3(384);
    cfg.dynamicSmemBytes = AUX_SMEM;
    cfg.stream = st;
    cudaLaunchAttribute at[1];
    at[0].id = cudaLaunchAttributeProgrammaticStreamSerialization;
    at[0].val.programmaticStreamSerializationAllowed = 1;
    cfg.attrs = at;
    cfg.numAttrs = 1;
    cudaLaunchKernelEx(&cfg, aux_kernel, ap);
  }
  cleanup_kernel<<<16, 256, 0, st>>>();
}
```

```cpp
#include <cuda_runtime.h>
#include <cuda_bf16.h>
#include <cuda.h>
#include <stdint.h>

#define DEVINL __device__ __forceinline__

DEVINL uint32_t smem_u32(const void* p) { return (uint32_t)__cvta_generic_to_shared(p); }

DEVINL void mbar_init(uint32_t bar, uint32_t count) {
  asm volatile("mbarrier.init.shared::cta.b64 [%0], %1;" ::"r"(bar), "r"(count) : "memory");
}
DEVINL void mbar_arrive(uint32_t bar) {
  asm volatile("mbarrier.arrive.shared::cta.b64 _, [%0];" ::"r"(bar) : "memory");
}
DEVINL void mbar_arrive_expect_tx(uint32_t bar, uint32_t bytes) {
  asm volatile("mbarrier.arrive.expect_tx.shared::cta.b64 _, [%0], %1;" ::"r"(bar), "r"(bytes) : "memory");
}
DEVINL bool mbar_try_wait(uint32_t bar, uint32_t parity) {
  uint32_t done;
  asm volatile(
      "{\n.reg .pred p;\nmbarrier.try_wait.parity.shared::cta.b64 p, [%1], %2;\nselp.u32 %0, 1, 0, p;\n}"
      : "=r"(done)
      : "r"(bar), "r"(parity)
      : "memory");
  return done != 0;
}
__device__ unsigned g_abort;
DEVINL void mbar_wait(uint32_t bar, uint32_t parity) {
  asm volatile(
      "{\n.reg .pred p;\n.reg .u32 n;\nmov.u32 n, 0;\n"
      "WAIT_LOOP:\n"
      "mbarrier.try_wait.parity.shared::cta.b64 p, [%0], %1;\n"
      "@p bra WAIT_DONE;\n"
      "add.u32 n, n, 1;\n"
      "setp.lt.u32 p, n, 16777216;\n"
      "@p bra WAIT_LOOP;\n"
      "trap;\n"
      "WAIT_DONE:\n}"
      ::"r"(bar), "r"(parity) : "memory");
}
DEVINL void bar_sync(int id, int n) { asm volatile("bar.sync %0, %1;" ::"r"(id), "r"(n) : "memory"); }
DEVINL void bar_arrive(int id, int n) { asm volatile("bar.arrive %0, %1;" ::"r"(id), "r"(n) : "memory"); }
DEVINL void fence_proxy_async() { asm volatile("fence.proxy.async.shared::cta;" ::: "memory"); }
DEVINL void fence_proxy_async_all() { asm volatile("fence.proxy.async;" ::: "memory"); }

DEVINL uint32_t mapa(uint32_t addr, uint32_t rank) {
  uint32_t r;
  asm volatile("mapa.shared::cluster.u32 %0, %1, %2;" : "=r"(r) : "r"(addr), "r"(rank));
  return r;
}
DEVINL void st_async_v4(uint32_t dst, uint32_t a, uint32_t b, uint32_t c, uint32_t d, uint32_t bar) {
  asm volatile("st.async.weak.shared::cluster.mbarrier::complete_tx::bytes.v4.u32 [%0], {%1,%2,%3,%4}, [%5];" ::"r"(dst),
               "r"(a), "r"(b), "r"(c), "r"(d), "r"(bar)
               : "memory");
}
DEVINL void st_async_v2(uint32_t dst, uint32_t a, uint32_t b, uint32_t bar) {
  asm volatile("st.async.weak.shared::cluster.mbarrier::complete_tx::bytes.v2.u32 [%0], {%1,%2}, [%3];" ::"r"(dst), "r"(a),
               "r"(b), "r"(bar)
               : "memory");
}
DEVINL void cluster_sync_all() {
  asm volatile("barrier.cluster.arrive.release.aligned;\nbarrier.cluster.wait.acquire.aligned;" ::: "memory");
}

DEVINL void tma_load_2d(uint32_t dst, const CUtensorMap* tm, int c0, int c1, uint32_t bar) {
  asm volatile(
      "cp.async.bulk.tensor.2d.shared::cluster.global.mbarrier::complete_tx::bytes [%0], [%1, {%3, %4}], [%2];" ::"r"(dst),
      "l"(tm), "r"(bar), "r"(c0), "r"(c1)
      : "memory");
}
DEVINL void tma_store_2d(const CUtensorMap* tm, uint32_t src, int c0, int c1) {
  asm volatile("cp.async.bulk.tensor.2d.global.shared::cta.bulk_group [%0, {%2, %3}], [%1];" ::"l"(tm), "r"(src), "r"(c0),
               "r"(c1)
               : "memory");
}
DEVINL void bulk_commit() { asm volatile("cp.async.bulk.commit_group;" ::: "memory"); }
DEVINL void bulk_wait_read0() { asm volatile("cp.async.bulk.wait_group.read 0;" ::: "memory"); }
DEVINL void bulk_wait0() { asm volatile("cp.async.bulk.wait_group 0;" ::: "memory"); }

DEVINL uint4 ld_rlx_v4(const void* p) {
  uint4 v;
  asm volatile("ld.relaxed.gpu.global.v4.u32 {%0,%1,%2,%3}, [%4];" : "=r"(v.x), "=r"(v.y), "=r"(v.z), "=r"(v.w) : "l"(p) : "memory");
  return v;
}
DEVINL uint32_t ld_rlx_u32(const void* p) {
  uint32_t v;
  asm volatile("ld.relaxed.gpu.global.u32 %0, [%1];" : "=r"(v) : "l"(p) : "memory");
  return v;
}
DEVINL void st_rlx_v4(void* p, uint32_t a, uint32_t b, uint32_t c, uint32_t d) {
  asm volatile("st.relaxed.gpu.global.v4.u32 [%0], {%1,%2,%3,%4};" ::"l"(p), "r"(a), "r"(b), "r"(c), "r"(d) : "memory");
}
DEVINL void st_rlx_u32(void* p, uint32_t a) { asm volatile("st.relaxed.gpu.global.u32 [%0], %1;" ::"l"(p), "r"(a) : "memory"); }
DEVINL uint32_t ld_acq_u32(const void* p) {
  uint32_t v;
  asm volatile("ld.acquire.gpu.global.u32 %0, [%1];" : "=r"(v) : "l"(p) : "memory");
  return v;
}
DEVINL void red_release_add(void* p, uint32_t v) {
  asm volatile("red.release.gpu.global.add.u32 [%0], %1;" ::"l"(p), "r"(v) : "memory");
}

DEVINL void red_relaxed_add(void* p, uint32_t v) {
  asm volatile("red.relaxed.gpu.global.add.u32 [%0], %1;" ::"l"(p), "r"(v) : "memory");
}
DEVINL void tma_prefetch_2d(const CUtensorMap* tm, int c0, int c1) {
  asm volatile("cp.async.bulk.prefetch.tensor.2d.L2.global [%0, {%1, %2}];" ::"l"(tm), "r"(c0), "r"(c1) : "memory");
}
DEVINL void ldsm_x4(uint32_t (&r)[4], uint32_t addr) {
  asm volatile("ldmatrix.sync.aligned.m8n8.x4.shared.b16 {%0,%1,%2,%3}, [%4];" : "=r"(r[0]), "=r"(r[1]), "=r"(r[2]), "=r"(r[3]) : "r"(addr) : "memory");
}
DEVINL void ldsm_x4_t(uint32_t (&r)[4], uint32_t addr) {
  asm volatile("ldmatrix.sync.aligned.m8n8.x4.trans.shared.b16 {%0,%1,%2,%3}, [%4];" : "=r"(r[0]), "=r"(r[1]), "=r"(r[2]), "=r"(r[3]) : "r"(addr) : "memory");
}
DEVINL void ldsm_x2(uint32_t& r0, uint32_t& r1, uint32_t addr) {
  asm volatile("ldmatrix.sync.aligned.m8n8.x2.shared.b16 {%0,%1}, [%2];" : "=r"(r0), "=r"(r1) : "r"(addr) : "memory");
}
DEVINL void ldsm_x1(uint32_t& r0, uint32_t addr) {
  asm volatile("ldmatrix.sync.aligned.m8n8.x1.shared.b16 {%0}, [%1];" : "=r"(r0) : "r"(addr) : "memory");
}
DEVINL void stsm_x4_t(uint32_t addr, uint32_t r0, uint32_t r1, uint32_t r2, uint32_t r3) {
  asm volatile("stmatrix.sync.aligned.m8n8.x4.trans.shared.b16 [%0], {%1,%2,%3,%4};" ::"r"(addr), "r"(r0), "r"(r1), "r"(r2), "r"(r3) : "memory");
}
DEVINL void stsm_x2_t(uint32_t addr, uint32_t r0, uint32_t r1) {
  asm volatile("stmatrix.sync.aligned.m8n8.x2.trans.shared.b16 [%0], {%1,%2};" ::"r"(addr), "r"(r0), "r"(r1) : "memory");
}
DEVINL void mma16816(float (&d)[4], uint32_t a0, uint32_t a1, uint32_t a2, uint32_t a3, uint32_t b0, uint32_t b1) {
  asm volatile("mma.sync.aligned.m16n8k16.row.col.f32.bf16.bf16.f32 {%0,%1,%2,%3}, {%4,%5,%6,%7}, {%8,%9}, {%0,%1,%2,%3};"
               : "+f"(d[0]), "+f"(d[1]), "+f"(d[2]), "+f"(d[3])
               : "r"(a0), "r"(a1), "r"(a2), "r"(a3), "r"(b0), "r"(b1));
}
DEVINL void mma1688(float (&d)[4], uint32_t a0, uint32_t a1, uint32_t b0) {
  asm volatile("mma.sync.aligned.m16n8k8.row.col.f32.bf16.bf16.f32 {%0,%1,%2,%3}, {%4,%5}, {%6}, {%0,%1,%2,%3};"
               : "+f"(d[0]), "+f"(d[1]), "+f"(d[2]), "+f"(d[3])
               : "r"(a0), "r"(a1), "r"(b0));
}
DEVINL uint32_t pack_bf16(float lo, float hi) {
  uint32_t r;
  asm("cvt.rn.bf16x2.f32 %0, %1, %2;" : "=r"(r) : "f"(hi), "f"(lo));
  return r;
}
DEVINL void wg_fence() { asm volatile("wgmma.fence.sync.aligned;" ::: "memory"); }
DEVINL void wg_commit() { asm volatile("wgmma.commit_group.sync.aligned;" ::: "memory"); }
template <int N>
DEVINL void wg_wait() { asm volatile("wgmma.wait_group.sync.aligned %0;" ::"n"(N) : "memory"); }

DEVINL uint64_t make_desc(uint32_t addr, uint32_t lbo, uint32_t sbo, uint32_t swz) {
  return (uint64_t)((addr & 0x3FFFF) >> 4) | ((uint64_t)(lbo >> 4) << 16) | ((uint64_t)(sbo >> 4) << 32) | ((uint64_t)swz << 62);
}

constexpr int SEQ = 2048, DM = 640, NH = 32, DH = 192, SEG = 32, NSEG = 64, HD = NH * DH, FF = 1536;
constexpr int NSLOT = 4, NREP = 1, NUNIT = 80;
constexpr int XST = 8;
__device__ __nv_bfloat16 g_q[SEQ * HD];
__device__ __nv_bfloat16 g_k[NSEG * 40 * HD];
__device__ __nv_bfloat16 g_vT[NSEG * HD * 40];
constexpr uint32_t H1_SLOT = NH * NUNIT * 128, H2_SLOT = NREP * NUNIT * 128, H2_BASE = NSLOT * H1_SLOT;
__device__ uint4 g_xch[(H2_BASE + NSLOT * H2_SLOT) / 16];
__device__ unsigned g_segflag[NSEG];

constexpr int OFF_WQ = 0;
constexpr int OFF_WO = 81920;
constexpr int OFF_X = 163840;
constexpr int OFF_KT = OFF_X + XST * 4096;
constexpr int OFF_QX = OFF_KT + 5120;
constexpr int OFF_T9 = OFF_QX;
constexpr int OFF_MEM = OFF_T9 + 6144;
constexpr int OFF_VT = OFF_MEM + 10240;
constexpr int OFF_SM = OFF_VT + 5248;
constexpr int OFF_OM = OFF_SM + 3840;
constexpr int OFF_QM = OFF_OM;
constexpr int OFF_BAR = OFF_OM + 3072;
constexpr int OFF_P = OFF_BAR + 320;
constexpr int OFF_RED = OFF_P + 640;
constexpr int MAIN_SMEM = OFF_RED + 512;
static_assert(MAIN_SMEM <= 232448, "smem");
static_assert(OFF_KT % 1024 == 0, "align");

enum { B_XFULL = 0, B_XEMPTY = XST, B_XCL = 2 * XST, B_W = 3 * XST, B_MEM, B_SM, B_OM, B_T9, B_RAW, B_WQK, B_WFREE, B_W2, B_COUNT };

struct MainParams {
  CUtensorMap tm_x, tm_wq, tm_wk, tm_wv, tm_wo, tm_q, tm_k, tm_v;
  const __nv_bfloat16* mem0;
  int d1, d2, d3;
};

constexpr uint32_t DHI_SW128 = (1024u >> 4) | (1u << 30);
constexpr uint32_t DHI_NONE = (128u >> 4);
DEVINL uint32_t desc_lo(uint32_t addr, uint32_t lbo) { return ((addr & 0x3FFFF) >> 4) | ((lbo >> 4) << 16); }

template <int OFFB, int SCALE_D>
DEVINL void wgmma_rs_n32(float (&d)[16], uint32_t a0, uint32_t a1, uint32_t a2, uint32_t a3, uint32_t blo) {
  asm volatile(
      "{\n.reg .b64 db;\n.reg .b32 lo;\n.reg .pred p;\nsetp.ne.u32 p, %23, 0;\nadd.u32 lo, %20, %21;\nmov.b64 db, {lo, %22};\n"
      "wgmma.mma_async.sync.aligned.m64n32k16.f32.bf16.bf16 "
      "{%0,%1,%2,%3,%4,%5,%6,%7,%8,%9,%10,%11,%12,%13,%14,%15}, {%16,%17,%18,%19}, db, p, 1, 1, 0;\n}"
      : "+f"(d[0]), "+f"(d[1]), "+f"(d[2]), "+f"(d[3]), "+f"(d[4]), "+f"(d[5]), "+f"(d[6]), "+f"(d[7]), "+f"(d[8]),
        "+f"(d[9]), "+f"(d[10]), "+f"(d[11]), "+f"(d[12]), "+f"(d[13]), "+f"(d[14]), "+f"(d[15])
      : "r"(a0), "r"(a1), "r"(a2), "r"(a3), "r"(blo), "n"(OFFB >> 4), "n"(DHI_SW128), "n"(SCALE_D));
}
template <int OFFA, int OFFB, int SCALE_D>
DEVINL void wgmma_ss_n32_tA(float (&d)[16], uint32_t alo, uint32_t blo) {
  asm volatile(
      "{\n.reg .b64 da, db;\n.reg .b32 lo;\n.reg .pred p;\nsetp.ne.u32 p, %21, 0;\nadd.u32 lo, %16, %18;\nmov.b64 da, {lo, %20};\n"
      "add.u32 lo, %17, %19;\nmov.b64 db, {lo, %20};\n"
      "wgmma.mma_async.sync.aligned.m64n32k16.f32.bf16.bf16 "
      "{%0,%1,%2,%3,%4,%5,%6,%7,%8,%9,%10,%11,%12,%13,%14,%15}, da, db, p, 1, 1, 1, 0;\n}"
      : "+f"(d[0]), "+f"(d[1]), "+f"(d[2]), "+f"(d[3]), "+f"(d[4]), "+f"(d[5]), "+f"(d[6]), "+f"(d[7]), "+f"(d[8]),
        "+f"(d[9]), "+f"(d[10]), "+f"(d[11]), "+f"(d[12]), "+f"(d[13]), "+f"(d[14]), "+f"(d[15])
      : "r"(alo), "r"(blo), "n"(OFFA >> 4), "n"(OFFB >> 4), "n"(DHI_SW128), "n"(SCALE_D));
}
template <int OFFA, int OFFB, int TB, int SCALE_D>
DEVINL void wgmma_ss_n8_tA(float (&d)[4], uint32_t alo, uint32_t blo) {
  asm volatile(
      "{\n.reg .b64 da, db;\n.reg .b32 lo;\n.reg .pred p;\nsetp.ne.u32 p, %11, 0;\nadd.u32 lo, %4, %6;\nmov.b64 da, {lo, %8};\n"
      "add.u32 lo, %5, %7;\nmov.b64 db, {lo, %9};\n"
      "wgmma.mma_async.sync.aligned.m64n8k16.f32.bf16.bf16 {%0,%1,%2,%3}, da, db, p, 1, 1, 1, %10;\n}"
      : "+f"(d[0]), "+f"(d[1]), "+f"(d[2]), "+f"(d[3])
      : "r"(alo), "r"(blo), "n"(OFFA >> 4), "n"(OFFB >> 4), "n"(DHI_SW128), "n"(DHI_NONE), "n"(TB), "n"(SCALE_D));
}
template <int N> struct IC { static constexpr int value = N; };
template <int I, int N, class F> DEVINL void static_for(F&& f) {
  if constexpr (I < N) { f(IC<I>{}); static_for<I + 1, N>(f); }
}

DEVINL uint32_t enc_nz(uint32_t w) { return w ? w : 0x80008000u; }

DEVINL float ex2f(float x) { float y; asm("ex2.approx.ftz.f32 %0, %1;" : "=f"(y) : "f"(x)); return y; }
DEVINL float rcpf(float x) { float y; asm("rcp.approx.ftz.f32 %0, %1;" : "=f"(y) : "f"(x)); return y; }
DEVINL void lds_v2(float& x, float& y, uint32_t a) { asm volatile("ld.shared.v2.f32 {%0,%1}, [%2];" : "=f"(x), "=f"(y) : "r"(a) : "memory"); }
DEVINL void lds_v4(float4& v, uint32_t a) { asm volatile("ld.shared.v4.f32 {%0,%1,%2,%3}, [%4];" : "=f"(v.x), "=f"(v.y), "=f"(v.z), "=f"(v.w) : "r"(a) : "memory"); }
DEVINL void sts_u32(uint32_t a, uint32_t v) { asm volatile("st.shared.u32 [%0], %1;" ::"r"(a), "r"(v) : "memory"); }

DEVINL void publish_tile(char* h1, int tile, const float (&w)[4]) {
  st_rlx_u32(h1 + tile * 1024, enc_nz(pack_bf16(w[0], w[1])));
  st_rlx_u32(h1 + tile * 1024 + 128, enc_nz(pack_bf16(w[2], w[3])));
}

template <int IS_K>
DEVINL void proj_wg(const MainParams& p, uint32_t sb, int h, int j, int wid  , int lane) {
  const uint32_t bars = sb + OFF_BAR;
  uint32_t A[40][4];
  {
    mbar_wait(bars + 8 * B_WQK, 0);
    const uint32_t stg = sb + (IS_K ? OFF_WO : OFF_WQ);
    const uint32_t r = (lane & 7) + ((lane >> 4) << 3), ch = 2 * wid + ((lane >> 3) & 1);
    const uint32_t a0 = stg + r * 128 + ((ch ^ (r & 7)) << 4);
#pragma unroll
    for (int k = 0; k < 40; k++) ldsm_x4_t(A[k], a0 + k * 2048);
    __syncwarp();
    if (lane == 0) mbar_arrive(bars + 8 * B_WFREE);
  }
  const bool elected = (wid == 0 && lane == 0);
  const int wgbar = IS_K ? 2 : 1;
  const uint32_t st_off = (lane & 7) * 128 + (((2 * wid + ((lane >> 3) & 1)) ^ (lane & 7)) << 4);
  const uint32_t vrow = sb + OFF_VT + (wid * 16 + (lane >> 2)) * 80 + 4 * (lane & 3);
  const uint32_t xlo = desc_lo(sb + OFF_X, 16);
  const uint32_t memaddr = sb + OFF_MEM + lane * 16;

  for (int s = 0; s < NSEG; s++) {
    {
      float acc[16];
      const uint32_t g0 = 10u * s;
      static_for<0, 10>([&](auto cc) {
        constexpr int c = decltype(cc)::value;
        const uint32_t st = (g0 + c) % XST;
        mbar_wait(bars + 8 * (B_XFULL + st), ((g0 + c) / XST) & 1);
        wg_fence();
        const uint32_t xs = xlo + st * 256;
        static_for<0, 4>([&](auto kc) {
          constexpr int kk = decltype(kc)::value;
          wgmma_rs_n32<kk * 32, (c + kk > 0)>(acc, A[4 * c + kk][0], A[4 * c + kk][1], A[4 * c + kk][2], A[4 * c + kk][3], xs);
        });
        wg_commit();
        if constexpr (c > 0) {
          wg_wait<1>();
          if (lane == 0) mbar_arrive(bars + 8 * (B_XEMPTY + ((g0 + c - 1) % XST)));
        }
      });
      wg_wait<0>();
      if (lane == 0) mbar_arrive(bars + 8 * (B_XEMPTY + ((g0 + 9) % XST)));
      if (elected && s > 0) {
        bulk_wait0();
        red_relaxed_add(&g_segflag[s - 1], 1);
      }
      bar_sync(wgbar, 128);
      if (IS_K) {
#pragma unroll
        for (int t = 0; t < 4; t += 2)
          stsm_x4_t(sb + OFF_KT + 1024 + (t + (lane >> 4)) * 1024 + st_off, pack_bf16(acc[4 * t + 0], acc[4 * t + 1]), pack_bf16(acc[4 * t + 2], acc[4 * t + 3]),
                    pack_bf16(acc[4 * t + 4], acc[4 * t + 5]), pack_bf16(acc[4 * t + 6], acc[4 * t + 7]));
      } else {
#pragma unroll
        for (int t = 0; t < 4; t++) {
          sts_u32(vrow + 16 + 16 * t, pack_bf16(acc[4 * t + 0], acc[4 * t + 1]));
          sts_u32(vrow + 8 * 80 + 16 + 16 * t, pack_bf16(acc[4 * t + 2], acc[4 * t + 3]));
        }
      }
    }
    mbar_wait(bars + 8 * B_MEM, s & 1);
    const bool last = (s + 1 == NSEG);
    if (!IS_K && !last) bar_sync(10, 224);
    {
      float c0[4] = {0, 0, 0, 0}, c1[4] = {0, 0, 0, 0}, c2[4] = {0, 0, 0, 0}, c3[4] = {0, 0, 0, 0};
#pragma unroll
      for (int k = 0; k < 40; k += 4) {
        uint32_t b[4], b2[4];
        ldsm_x4_t(b, memaddr + k * 256);
        ldsm_x4_t(b2, memaddr + k * 256 + 512);
        mma16816(c0, A[k][0], A[k][1], A[k][2], A[k][3], b[0], b[1]);
        mma16816(c1, A[k + 1][0], A[k + 1][1], A[k + 1][2], A[k + 1][3], b[2], b[3]);
        mma16816(c2, A[k + 2][0], A[k + 2][1], A[k + 2][2], A[k + 2][3], b2[0], b2[1]);
        mma16816(c3, A[k + 3][0], A[k + 3][1], A[k + 3][2], A[k + 3][3], b2[2], b2[3]);
      }
#pragma unroll
      for (int i = 0; i < 4; i++) c0[i] = (c0[i] + c1[i]) + (c2[i] + c3[i]);
      if (IS_K) {
        stsm_x2_t(sb + OFF_KT + st_off, pack_bf16(c0[0], c0[1]), pack_bf16(c0[2], c0[3]));
      } else {
        sts_u32(vrow, pack_bf16(c0[0], c0[1]));
        sts_u32(vrow + 8 * 80, pack_bf16(c0[2], c0[3]));
      }
    }
    if (!last) {
      if (IS_K) {
        bar_sync(3, 256);
        if (wid < 3) {
          uint32_t a[4], a2[4], b[4], b2[4], c[4], c2[4];
          const int row = lane & 7, ch = lane >> 3;
          const uint32_t o1 = row * 128 + ((ch ^ row) << 4), o2 = row * 128 + (((ch + 4) ^ row) << 4);
          const uint32_t kb = sb + OFF_KT + wid * 2048;
          ldsm_x4(a, sb + OFF_QM + o1);
          ldsm_x4(b, kb + o1);
          ldsm_x4(a2, sb + OFF_QM + o2);
          ldsm_x4(b2, kb + o2);
          float s0[4] = {0, 0, 0, 0}, s1[4] = {0, 0, 0, 0}, u0[4] = {0, 0, 0, 0}, u1[4] = {0, 0, 0, 0};
          if (wid < 2) {
            ldsm_x4(c, kb + 1024 + o1);
            ldsm_x4(c2, kb + 1024 + o2);
          }
          mma16816(s0, a[0], 0, a[1], 0, b[0], b[1]);
          mma16816(s1, a2[0], 0, a2[1], 0, b2[0], b2[1]);
          mma16816(s0, a[2], 0, a[3], 0, b[2], b[3]);
          mma16816(s1, a2[2], 0, a2[3], 0, b2[2], b2[3]);
          const uint32_t x0 = __float_as_uint(s0[0] + s1[0]), x1 = __float_as_uint(s0[1] + s1[1]);
          const uint32_t dst = (sb & 0x00FFFFFFu) + OFF_SM + j * 1280 + wid * 512, bsm = (sb & 0x00FFFFFFu) + OFF_BAR + 8 * B_SM;
          if (wid < 2) {
            mma16816(u0, a[0], 0, a[1], 0, c[0], c[1]);
            mma16816(u1, a2[0], 0, a2[1], 0, c2[0], c2[1]);
            mma16816(u0, a[2], 0, a[3], 0, c[2], c[3]);
            mma16816(u1, a2[2], 0, a2[3], 0, c2[2], c2[3]);
            const uint32_t y0 = __float_as_uint(u0[0] + u1[0]), y1 = __float_as_uint(u0[1] + u1[1]);
#pragma unroll
            for (int r = 0; r < 3; r++) st_async_v4(dst + lane * 16 + (r << 24), x0, x1, y0, y1, bsm + (r << 24));
          } else {
#pragma unroll
            for (int r = 0; r < 3; r++) st_async_v2(dst + lane * 8 + (r << 24), x0, x1, bsm + (r << 24));
          }
          bar_arrive(10, 224);
        } else {
          if (lane == 0) mbar_arrive_expect_tx(bars + 8 * B_SM, 3840);
          mbar_wait(bars + 8 * B_SM, s & 1);
          const float sc = 0.07216878364870322f * 1.4426950408889634f;
          float sv[10];
#pragma unroll
          for (int i = 0; i < 10; i++) sv[i] = 0.f;
#pragma unroll
          for (int r = 0; r < 3; r++) {
            float4 u, v;
            float x, y;
            lds_v4(u, sb + OFF_SM + r * 1280 + lane * 16);
            lds_v4(v, sb + OFF_SM + r * 1280 + 512 + lane * 16);
            lds_v2(x, y, sb + OFF_SM + r * 1280 + 1024 + lane * 8);
            sv[0] += u.x; sv[1] += u.y; sv[2] += u.z; sv[3] += u.w;
            sv[4] += v.x; sv[5] += v.y; sv[6] += v.z; sv[7] += v.w;
            sv[8] += x; sv[9] += y;
          }
          float m = fmaxf(fmaxf(fmaxf(sv[0], sv[1]), fmaxf(sv[2], sv[3])), fmaxf(fmaxf(sv[4], sv[5]), fmaxf(sv[6], sv[7])));
          m = fmaxf(m, fmaxf(sv[8], sv[9])) * sc;
          const float mloc = m;
#pragma unroll
          for (int i = 0; i < 10; i++) sv[i] = ex2f(fmaf(sv[i], sc, -m));
          float sum = ((sv[0] + sv[1]) + (sv[2] + sv[3])) + ((sv[4] + sv[5]) + (sv[6] + sv[7])) + (sv[8] + sv[9]);
#pragma unroll
          for (int o = 1; o <= 2; o <<= 1) {
            const float mo = __shfl_xor_sync(0xffffffffu, m, o), so = __shfl_xor_sync(0xffffffffu, sum, o);
            const float mn = fmaxf(m, mo);
            sum = sum * ex2f(m - mn) + so * ex2f(mo - mn);
            m = mn;
          }
          const float f = ex2f(mloc - m) * rcpf(sum);
#pragma unroll
          for (int t = 0; t < 5; t++) sts_u32(sb + OFF_P + t * 128 + lane * 4, pack_bf16(sv[2 * t] * f, sv[2 * t + 1] * f));
          bar_arrive(9, 160);
        }
      } else {
        bar_arrive(6, 256);
      }
    }
    fence_proxy_async();
    bar_sync(wgbar, 128);
    if (elected) {
      if (IS_K) tma_store_2d(&p.tm_k, sb + OFF_KT, h * DH + j * 64, s * 40);
      else tma_store_2d(&p.tm_v, sb + OFF_VT, 0, (s * NH + h) * DH + j * 64);
      bulk_commit();
    }
    if (last) break;
    if (!IS_K && j == 0) {
      if (elected) mbar_arrive_expect_tx(bars + 8 * B_T9, 6144);
      mbar_wait(bars + 8 * B_T9, s & 1);
      const uint32_t t9 = sb + OFF_T9 + (wid * 32 + lane) * 16;
      float4 a, b, c;
      lds_v4(a, t9);
      lds_v4(b, t9 + 2048);
      lds_v4(c, t9 + 4096);
      char* h1 = (char*)g_xch + (s % NSLOT) * H1_SLOT + h * NUNIT * 128 + wid * 256 + lane * 4;
      const float w9[4] = {a.x + b.x + c.x, a.y + b.y + c.y, a.z + b.z + c.z, a.w + b.w + c.w};
      publish_tile(h1, 9, w9);
    }
    bar_sync(7, 384);
  }
  if (elected) {
    bulk_wait0();
    red_relaxed_add(&g_segflag[NSEG - 1], 1);
  }
}

template <int T, int FIRST>
DEVINL void wo_issue_slice(float (&w)[4], uint32_t wolo_sl, uint32_t omlo_sl) {
  wgmma_ss_n8_tA<T * 24576 + 0 * 2048, 0 * 256, 0, !FIRST>(w, wolo_sl, omlo_sl);
  wgmma_ss_n8_tA<T * 24576 + 1 * 2048, 1 * 256, 0, 1>(w, wolo_sl, omlo_sl);
  wgmma_ss_n8_tA<T * 24576 + 2 * 2048, 2 * 256, 0, 1>(w, wolo_sl, omlo_sl);
  wgmma_ss_n8_tA<T * 24576 + 3 * 2048, 3 * 256, 0, 1>(w, wolo_sl, omlo_sl);
}

DEVINL void q_wg(const MainParams& p, uint32_t sb, int h, int j, int wid, int lane) {
  const int tid128 = wid * 32 + lane;
  const bool elected = (tid128 == 0);
  const uint32_t bars = sb + OFF_BAR;
  const int g8 = lane >> 2;
  const uint32_t wqlo = desc_lo(sb + OFF_WQ, 16), memlo = desc_lo(sb + OFF_MEM, 128);
  const uint32_t st_off = (lane & 7) * 128 + (((2 * wid + ((lane >> 3) & 1)) ^ (lane & 7)) << 4);
  char* const h1base = (char*)g_xch + h * NUNIT * 128 + wid * 256 + lane * 4;

  mbar_wait(bars + 8 * B_W, 0);

  const uint32_t xlo = desc_lo(sb + OFF_X, 16);
  for (int s = 0; s < NSEG; s++) {
    {
      float acc[16];
      const uint32_t g0 = 10u * s;
      static_for<0, 10>([&](auto cc) {
        constexpr int c = decltype(cc)::value;
        const uint32_t st = (g0 + c) % XST;
        mbar_wait(bars + 8 * (B_XFULL + st), ((g0 + c) / XST) & 1);
        wg_fence();
        const uint32_t xs = xlo + st * 256;
        static_for<0, 4>([&](auto kc) {
          constexpr int kk = decltype(kc)::value;
          wgmma_ss_n32_tA<(4 * c + kk) * 2048, kk * 32, (c + kk > 0)>(acc, wqlo, xs);
        });
        wg_commit();
        if constexpr (c > 0) {
          wg_wait<1>();
          if (lane == 0) mbar_arrive(bars + 8 * (B_XEMPTY + ((g0 + c - 1) % XST)));
        }
      });
      wg_wait<0>();
      if (lane == 0) mbar_arrive(bars + 8 * (B_XEMPTY + ((g0 + 9) % XST)));
      if (elected && s > 0) {
        bulk_wait0();
        red_relaxed_add(&g_segflag[s - 1], 1);
      }
#pragma unroll
      for (int t = 0; t < 4; t += 2)
        stsm_x4_t(sb + OFF_QX + (t + (lane >> 4)) * 1024 + st_off, pack_bf16(acc[4 * t + 0], acc[4 * t + 1]), pack_bf16(acc[4 * t + 2], acc[4 * t + 3]),
                  pack_bf16(acc[4 * t + 4], acc[4 * t + 5]), pack_bf16(acc[4 * t + 6], acc[4 * t + 7]));
      fence_proxy_async();
      bar_sync(4, 128);
      if (elected && s + 1 == NSEG) { tma_store_2d(&p.tm_q, sb + OFF_QX, h * DH + j * 64, s * SEG); bulk_commit(); }
    }
    if (s + 1 == NSEG) break;
    mbar_wait(bars + 8 * B_MEM, s & 1);
    if (elected) { tma_store_2d(&p.tm_q, sb + OFF_QX, h * DH + j * 64, s * SEG); bulk_commit(); }
    {
      {
        float acc[4];
        wg_fence();
        static_for<0, 40>([&](auto kc) {
          constexpr int k = decltype(kc)::value;
          wgmma_ss_n8_tA<k * 2048, k * 256, 1, (k > 0)>(acc, wqlo, memlo);
        });
        wg_commit();
        if (elected) { mbar_arrive_expect_tx(bars + 8 * B_OM, 2048); bulk_wait_read0(); }
        wg_wait<0>();
        stsm_x2_t(sb + OFF_QM + st_off, pack_bf16(acc[0], acc[1]), pack_bf16(acc[2], acc[3]));
      }
      bar_sync(3, 256);
      bar_sync(6, 256);
      uint32_t vb0[4], vb1[4], vb2, vb3, P[5];
      {
        uint32_t base = sb + OFF_VT + (wid * 16 + (lane & 7)) * 80 + (lane >> 3) * 16;
        ldsm_x4(vb0, base);
        ldsm_x4(vb1, base + 8 * 80);
        uint32_t b2 = sb + OFF_VT + (wid * 16 + (lane & 7) + ((lane >> 3) & 1) * 8) * 80 + 64;
        ldsm_x2(vb2, vb3, b2);
      }
      bar_sync(9, 160);
#pragma unroll
      for (int t = 0; t < 5; t++) asm volatile("ld.shared.u32 %0, [%1];" : "=r"(P[t]) : "r"(sb + OFF_P + t * 128 + lane * 4) : "memory");
      float o0[4] = {0, 0, 0, 0}, o1[4] = {0, 0, 0, 0}, o2[4] = {0, 0, 0, 0}, o3[4] = {0, 0, 0, 0};
      mma16816(o0, P[0], 0, P[1], 0, vb0[0], vb0[1]);
      mma16816(o1, P[0], 0, P[1], 0, vb1[0], vb1[1]);
      mma16816(o2, P[2], 0, P[3], 0, vb0[2], vb0[3]);
      mma16816(o3, P[2], 0, P[3], 0, vb1[2], vb1[3]);
      mma1688(o0, P[4], 0, vb2);
      mma1688(o1, P[4], 0, vb3);
      uint32_t wa = pack_bf16(o0[0] + o2[0], o0[1] + o2[1]), wb = pack_bf16(o1[0] + o3[0], o1[1] + o3[1]);
      const bool odd = lane & 1, up = lane & 2;
      uint32_t rcv = __shfl_xor_sync(0xffffffffu, odd ? wa : wb, 1);
      uint32_t p0 = odd ? rcv : wa, p1 = odd ? wb : rcv;
      uint32_t q0 = __shfl_xor_sync(0xffffffffu, p0, 2), q1 = __shfl_xor_sync(0xffffffffu, p1, 2);
      uint32_t r0 = up ? q0 : p0, r1 = up ? q1 : p1, r2 = up ? p0 : q0, r3 = up ? p1 : q1;
      const uint32_t oa = (sb & 0x00FFFFFFu) + OFF_OM + (8 * j + 2 * wid + (lane & 1)) * 128 + g8 * 16;
      const int peer = (up ? (j == 2 ? 1 : 2) : (j == 0 ? 1 : 0));
      st_async_v4(oa + (peer << 24), r0, r1, r2, r3, (sb & 0x00FFFFFFu) + OFF_BAR + 8 * B_OM + (peer << 24));
      if (!up) asm volatile("st.shared.v4.u32 [%0], {%1,%2,%3,%4};" ::"r"(oa + (sb & 0xFF000000u)), "r"(r0), "r"(r1), "r"(r2), "r"(r3) : "memory");
    }
    fence_proxy_async();
    bar_sync(4, 128);
    {
      char* h1 = h1base + (s % NSLOT) * H1_SLOT;
      const uint32_t wolo = desc_lo(sb + OFF_WO, 16), omlo = desc_lo(sb + OFF_OM, 128);
      float w9[4], w0[4], w1[4], w2[4];
      const uint32_t om_own = omlo + j * (1024 >> 4);
      if (s == 0) mbar_wait(bars + 8 * B_W2, 0);
      wg_fence();
      wgmma_ss_n8_tA<73728 + 0 * 2048, 0 * 256, 0, 0>(w9, wolo, om_own);
      wgmma_ss_n8_tA<73728 + 1 * 2048, 1 * 256, 0, 1>(w9, wolo, om_own);
      wgmma_ss_n8_tA<73728 + 2 * 2048, 2 * 256, 0, 1>(w9, wolo, om_own);
      wgmma_ss_n8_tA<73728 + 3 * 2048, 3 * 256, 0, 1>(w9, wolo, om_own);
      wg_commit();
      const int j1 = (j == 2) ? 0 : j + 1, j2 = (j == 0) ? 2 : j - 1;
      wo_issue_slice<0, 1>(w0, wolo + j * 512, omlo + j * 64);
      wo_issue_slice<1, 1>(w1, wolo + j * 512, omlo + j * 64);
      wo_issue_slice<2, 1>(w2, wolo + j * 512, omlo + j * 64);
      wg_commit();
      wg_wait<1>();
      st_async_v4((sb & 0x00FFFFFFu) + OFF_T9 + j * 2048 + tid128 * 16, __float_as_uint(w9[0]), __float_as_uint(w9[1]),
                  __float_as_uint(w9[2]), __float_as_uint(w9[3]), (sb & 0x00FFFFFFu) + OFF_BAR + 8 * B_T9);
      mbar_wait(bars + 8 * B_OM, s & 1);
      fence_proxy_async();
      wg_fence();
      wo_issue_slice<0, 0>(w0, wolo + j1 * 512, omlo + j1 * 64);
      wo_issue_slice<0, 0>(w0, wolo + j2 * 512, omlo + j2 * 64);
      wg_commit();
      wo_issue_slice<1, 0>(w1, wolo + j1 * 512, omlo + j1 * 64);
      wo_issue_slice<1, 0>(w1, wolo + j2 * 512, omlo + j2 * 64);
      wg_commit();
      wo_issue_slice<2, 0>(w2, wolo + j1 * 512, omlo + j1 * 64);
      wo_issue_slice<2, 0>(w2, wolo + j2 * 512, omlo + j2 * 64);
      wg_commit();
      wg_wait<2>();
      publish_tile(h1, 3 * j + 0, w0);
      wg_wait<1>();
      publish_tile(h1, 3 * j + 1, w1);
      wg_wait<0>();
      bar_arrive(7, 384);
      publish_tile(h1, 3 * j + 2, w2);
      bar_arrive(8, 128 + 96);
    }
  }
  if (elected) {
    bulk_wait0();
    red_relaxed_add(&g_segflag[NSEG - 1], 1);
  }
}

DEVINL bool nz4(const uint4& v) { return v.x != 0 && v.y != 0 && v.z != 0 && v.w != 0; }
DEVINL uint32_t clk32() { uint32_t c; asm volatile("mov.u32 %0, %clock;" : "=r"(c)); return c; }
DEVINL void spin_clk(int n) {
  uint32_t t = clk32();
  while ((int)(clk32() - t) < n) {}
}

DEVINL void comm_wg(const MainParams& p, uint32_t sb, int h, int j, int cta, int wid, int lane) {
  const uint32_t bars = sb + OFF_BAR;
  if (wid == 0) {
    if (lane == 0) {
      mbar_arrive_expect_tx(bars + 8 * B_WQK, 2 * 81920);
      for (int c = 0; c < 5; c++) {
        tma_load_2d(sb + OFF_WO + c * 16384, &p.tm_wk, h * DH + j * 64, c * 128, bars + 8 * B_WQK);
        tma_load_2d(sb + OFF_WQ + c * 16384, &p.tm_wv, h * DH + j * 64, c * 128, bars + 8 * B_WQK);
      }
      auto x_chunk = [&](uint32_t g, uint32_t ck, uint32_t sg) {
        const uint32_t st = g % XST, issuer = g % 3;
        if (g >= XST) mbar_wait(bars + 8 * (B_XEMPTY + st), ((g / XST) - 1) & 1);
        mbar_arrive_expect_tx(bars + 8 * (B_XFULL + st), 4096);
        asm volatile("mbarrier.arrive.shared::cluster.b64 _, [%0];" ::"r"((sb & 0x00FFFFFFu) + OFF_BAR + 8 * (B_XCL + st) + (issuer << 24)) : "memory");
        if (issuer == (uint32_t)j) {
          mbar_wait(bars + 8 * (B_XCL + st), (g / (3 * XST)) & 1);
          asm volatile(
              "cp.async.bulk.tensor.2d.shared::cluster.global.mbarrier::complete_tx::bytes.multicast::cluster [%0], [%1, {%3, %4}], [%2], %5;" ::"r"(
                  sb + OFF_X + st * 4096),
              "l"(&p.tm_x), "r"(bars + 8 * (B_XFULL + st)), "r"(ck * 64), "r"(sg * SEG), "h"((uint16_t)7u)
              : "memory");
        }
      };
      for (uint32_t g = 0; g < XST; g++) x_chunk(g, g, 0);
      if (cta < 20) tma_prefetch_2d(&p.tm_x, (cta % 10) * 64, (1 + cta / 10) * SEG);
      mbar_wait(bars + 8 * B_WFREE, 0);
      mbar_arrive_expect_tx(bars + 8 * B_W, 81920);
      for (int c = 0; c < 5; c++) tma_load_2d(sb + OFF_WQ + c * 16384, &p.tm_wq, h * DH + j * 64, c * 128, bars + 8 * B_W);
      mbar_arrive_expect_tx(bars + 8 * B_W2, 81920);
      for (int t = 0; t < 3; t++)
        for (int c = 0; c < 3; c++)
          tma_load_2d(sb + OFF_WO + t * 24576 + c * 8192, &p.tm_wo, (3 * j + t) * 64, h * DH + c * 64, bars + 8 * B_W2);
      tma_load_2d(sb + OFF_WO + 73728, &p.tm_wo, 9 * 64, h * DH + j * 64, bars + 8 * B_W2);
      uint32_t ck = XST, sg = 0;
#pragma unroll 1
      for (uint32_t g = XST; g < 10u * NSEG; g++) {
        if (ck == 10) {
          ck = 0; sg++;
          if (cta < 10 && sg + 2 < NSEG) tma_prefetch_2d(&p.tm_x, cta * 64, (sg + 2) * SEG);
        }
        x_chunk(g, ck, sg);
        ck++;
      }
    }
    return;
  }
  const int pt = (wid - 1) * 32 + lane;
  for (int d = pt; d < DM; d += 96) {
    uint32_t w[4];
#pragma unroll
    for (int r = 0; r < 4; r++) {
      uint32_t lo = __bfloat16_as_ushort(p.mem0[(2 * r) * DM + d]), hi = __bfloat16_as_ushort(p.mem0[(2 * r + 1) * DM + d]);
      w[r] = lo | (hi << 16);
    }
    asm volatile("st.shared.v4.u32 [%0], {%1,%2,%3,%4};" ::"r"(sb + OFF_MEM + d * 16), "r"(w[0]), "r"(w[1]), "r"(w[2]), "r"(w[3]) : "memory");
  }
  fence_proxy_async();
  bar_sync(5, 96);
  if (pt == 0) mbar_arrive(bars + 8 * B_MEM);

  const bool is_red = cta < NUNIT;
  const int dly2 = is_red ? p.d2 : p.d3;
  char* const xb = (char*)g_xch;
  uint32_t ptv = pt;
  uint32_t rawph = 0;
#pragma unroll 1
  for (int x = 0; x + 1 < NSEG; x++) {
    const uint32_t slot = x % NSLOT;
    mbar_wait(bars + 8 * B_MEM, x & 1);
    asm volatile("" : "+r"(ptv));
    bar_sync(8, 128 + 96);
    if (is_red) {
      const uint32_t w3 = ptv >> 5, ln = ptv & 31;
      char* src = xb + slot * H1_SLOT + ((11 * w3) * NUNIT + cta) * 128 + ln * 4;
      spin_clk(p.d1);
      uint32_t v[11];
#pragma unroll
      for (int c = 0; c < 10; c++) v[c] = ld_rlx_u32(src + c * NUNIT * 128);
      v[10] = (w3 < 2) ? ld_rlx_u32(src + 10 * NUNIT * 128) : 0x80008000u;
      uint32_t n = 0;
      while (true) {
        bool ok = true;
#pragma unroll
        for (int c = 0; c < 11; c++) ok = ok && (v[c] != 0);
        if (__all_sync(0xffffffffu, ok)) break;
#pragma unroll
        for (int c = 0; c < 11; c++)
          if (v[c] == 0) v[c] = ld_rlx_u32(src + c * NUNIT * 128);
        if (++n > (1u << 22)) __trap();
      }
      float a0 = 0.f, a1 = 0.f, b0 = 0.f, b1 = 0.f;
#pragma unroll
      for (int c = 0; c < 10; c += 2) {
        a0 += __uint_as_float(v[c] << 16); a1 += __uint_as_float(v[c] & 0xffff0000u);
        b0 += __uint_as_float(v[c + 1] << 16); b1 += __uint_as_float(v[c + 1] & 0xffff0000u);
      }
      a0 += __uint_as_float(v[10] << 16) + b0; a1 += __uint_as_float(v[10] & 0xffff0000u) + b1;
      if (w3 != 0) asm volatile("st.shared.v2.f32 [%0], {%1,%2};" ::"r"(sb + OFF_RED + (ptv - 32) * 8), "f"(a0), "f"(a1) : "memory");
      bar_sync(5, 96);
      if (w3 == 0) {
        float c0, c1, d0, d1;
        lds_v2(c0, c1, sb + OFF_RED + ln * 8);
        lds_v2(d0, d1, sb + OFF_RED + 256 + ln * 8);
        const uint32_t w = enc_nz(pack_bf16(a0 + c0 + d0, a1 + c1 + d1));
        char* dst = xb + H2_BASE + slot * H2_SLOT + cta * 128 + ln * 4;
#pragma unroll
        for (int r = 0; r < NREP; r++) st_rlx_u32(dst + r * NUNIT * 128, w);
      }
    }
    spin_clk(dly2);
    uint32_t n = 0;
    while (true) {
      if (ptv == 0) {
        mbar_arrive_expect_tx(bars + 8 * B_RAW, 10240);
        asm volatile("cp.async.bulk.shared::cluster.global.mbarrier::complete_tx::bytes [%0], [%1], %2, [%3];" ::"r"(sb + OFF_MEM),
                     "l"(xb + H2_BASE + slot * H2_SLOT + (h % NREP) * NUNIT * 128), "r"(10240), "r"(bars + 8 * B_RAW)
                     : "memory");
      }
      if (n == 0) {
        if (is_red) {
          char* src = xb + slot * H1_SLOT + ((11 * (ptv >> 5)) * NUNIT + cta) * 128 + (ptv & 31) * 4;
#pragma unroll
          for (int c = 0; c < 10; c++) st_rlx_u32(src + c * NUNIT * 128, 0);
          if (ptv < 64) st_rlx_u32(src + 10 * NUNIT * 128, 0);
        }
        if (x >= 1 && h < NREP && j == 0) {
          char* old = xb + H2_BASE + ((x - 1) % NSLOT) * H2_SLOT + h * NUNIT * 128 + ptv * 16;
#pragma unroll
          for (int k = 0; k < 6; k++) st_rlx_v4(old + k * 96 * 16, 0, 0, 0, 0);
          if (ptv < DM - 6 * 96) st_rlx_v4(old + 6 * 96 * 16, 0, 0, 0, 0);
        }
      }
      mbar_wait(bars + 8 * B_RAW, rawph);
      rawph ^= 1;
      bool ok = true;
#pragma unroll
      for (int k = 0; k < 7; k++) {
        if (k < 6 || ptv < DM - 6 * 96) {
          uint4 t;
          asm volatile("ld.shared.v4.u32 {%0,%1,%2,%3}, [%4];" : "=r"(t.x), "=r"(t.y), "=r"(t.z), "=r"(t.w) : "r"(sb + OFF_MEM + (ptv + k * 96) * 16) : "memory");
          ok = ok && nz4(t);
        }
      }
      uint32_t all;
      asm volatile("{\n.reg .pred p, q;\nsetp.ne.u32 p, %1, 0;\nbar.red.and.pred q, 5, 96, p;\nselp.u32 %0, 1, 0, q;\n}" : "=r"(all) : "r"((uint32_t)ok) : "memory");
      if (all) break;
      if (++n > (1u << 22)) __trap();
    }
    if (ptv == 0) mbar_arrive(bars + 8 * B_MEM);
  }
}

__global__ void __launch_bounds__(512, 1) main_kernel(const __grid_constant__ MainParams p) {
  extern __shared__ __align__(1024) uint8_t smem[];
  const uint32_t sb = smem_u32(smem);
  const int tid = threadIdx.x, wg = tid >> 7, wid = (tid >> 5) & 3, lane = tid & 31;
  const int cta = blockIdx.x;
  const int h = cta / 3, j = cta % 3;
  if (tid == 0) {
    const uint32_t bars = sb + OFF_BAR;
    for (int i = 0; i < XST; i++) {
      mbar_init(bars + 8 * (B_XFULL + i), 1);
      mbar_init(bars + 8 * (B_XEMPTY + i), 12);
      mbar_init(bars + 8 * (B_XCL + i), 3);
    }
    mbar_init(bars + 8 * B_W, 1);
    mbar_init(bars + 8 * B_MEM, 1);
    mbar_init(bars + 8 * B_RAW, 1);
    mbar_init(bars + 8 * B_WQK, 1);
    mbar_init(bars + 8 * B_W2, 1);
    mbar_init(bars + 8 * B_WFREE, 8);
    mbar_init(bars + 8 * B_SM, 1);
    mbar_init(bars + 8 * B_OM, 1);
    mbar_init(bars + 8 * B_T9, 1);
    asm volatile("fence.mbarrier_init.release.cluster;" ::: "memory");
  }
  __syncthreads();
  cluster_sync_all();
  asm volatile("griddepcontrol.launch_dependents;" ::: "memory");
  if (wg == 0) {
    asm volatile("setmaxnreg.inc.sync.aligned.u32 208;");
    proj_wg<0>(p, sb, h, j, wid, lane);
  } else if (wg == 1) {
    asm volatile("setmaxnreg.inc.sync.aligned.u32 208;");
    proj_wg<1>(p, sb, h, j, wid, lane);
  } else if (wg == 2) {
    asm volatile("setmaxnreg.dec.sync.aligned.u32 56;");
    q_wg(p, sb, h, j, wid, lane);
  } else {
    asm volatile("setmaxnreg.dec.sync.aligned.u32 40;");
    comm_wg(p, sb, h, j, cta, wid, lane);
  }
}

constexpr int WSPLIT = 4, WSPLIT_LAST = 16;
__device__ __nv_bfloat16 g_hid[SEQ * FF];
__device__ __nv_bfloat16 g_o[SEQ * HD];
__device__ unsigned g_ctr, g_done;
__device__ unsigned g_f1flag[16], g_f2flag[40], g_atflag[8], g_wcnt[40], g_gflag[16];
__device__ float g_gate[SEQ];
__device__ uint4 g_bfrag[40 * 16 * 256];
__device__ float g_wpart[(35 * WSPLIT + 5 * WSPLIT_LAST) * 256 * 128];

struct AuxParams {
  CUtensorMap tm_x128, tm_wg, tm_wu, tm_hid, tm_wd, tm_o, tm_wo, tm_q, tm_k, tm_v3, tm_ost, tm_hst, tm_out;
  const __nv_bfloat16* ax;
  const __nv_bfloat16* gate_w;
  __nv_bfloat16* out;
};

constexpr int N_G = 16, N_F1 = 16 * 12, N_F2 = 8 * 5, N_AT_TILE = 64, N_W_TILE = 5 * WSPLIT;
constexpr int N_PER_TILE = N_AT_TILE + N_W_TILE;
constexpr int N_ITEMS = N_G + N_F1 + N_F2 + 7 * N_PER_TILE + N_AT_TILE + 5 * WSPLIT_LAST;
constexpr int N_TAIL_START = N_ITEMS - 5 * WSPLIT_LAST - 24;
constexpr int AST = 4, AST_BYTES = 49152;
constexpr int AUX_OFF_STG = AST * AST_BYTES;
constexpr int AUX_OFF_BAR = AUX_OFF_STG + 32768;
constexpr int AUX_SMEM = AUX_OFF_BAR + 256;
enum { AB_FULL = 0, AB_EMPTY = AST, AB_QFULL = 2 * AST, AB_QEMPTY = 2 * AST + 2 };

#define ACC_REGS_64 "%0,%1,%2,%3,%4,%5,%6,%7,%8,%9,%10,%11,%12,%13,%14,%15,%16,%17,%18,%19,%20,%21,%22,%23,%24,%25,%26,%27,%28,%29,%30,%31," \
                    "%32,%33,%34,%35,%36,%37,%38,%39,%40,%41,%42,%43,%44,%45,%46,%47,%48,%49,%50,%51,%52,%53,%54,%55,%56,%57,%58,%59,%60,%61,%62,%63"
#define ACC8(d, o) "+f"(d[o + 0]), "+f"(d[o + 1]), "+f"(d[o + 2]), "+f"(d[o + 3]), "+f"(d[o + 4]), "+f"(d[o + 5]), "+f"(d[o + 6]), "+f"(d[o + 7])
#define ACC64(d) ACC8(d, 0), ACC8(d, 8), ACC8(d, 16), ACC8(d, 24), ACC8(d, 32), ACC8(d, 40), ACC8(d, 48), ACC8(d, 56)
DEVINL void wgmma_n128_tB(float (&d)[64], uint64_t da, uint64_t db, int scale_d) {
  asm volatile(
      "{\n.reg .pred p;\nsetp.ne.u32 p, %66, 0;\n"
      "wgmma.mma_async.sync.aligned.m64n128k16.f32.bf16.bf16 {" ACC_REGS_64 "}, %64, %65, p, 1, 1, 0, 1;\n}"
      : ACC64(d)
      : "l"(da), "l"(db), "r"(scale_d));
}
DEVINL void mbar_arrive_cnt(uint32_t bar, uint32_t cnt) {
  asm volatile("mbarrier.arrive.shared::cta.b64 _, [%0], %1;" ::"r"(bar), "r"(cnt) : "memory");
}
DEVINL float bf16r(float x) { return __bfloat162float(__float2bfloat16_rn(x)); }
DEVINL float sigmoidf_(float x) { return rcpf(1.0f + ex2f(-1.4426950408889634f * x)); }

DEVINL void wait_flag(const unsigned* f, unsigned target) {
  uint32_t n = 0;
  while (ld_acq_u32(f) < target) {
    __nanosleep(100);
    if (++n > (1u << 24)) __trap();
  }
}

DEVINL void gate_rows(const __nv_bfloat16* ax, const __nv_bfloat16* gw, int row0, int lane) {
  uint4 w[3];
#pragma unroll
  for (int i = 0; i < 3; i++) w[i] = (lane + 32 * i < 80) ? __ldg((const uint4*)gw + lane + 32 * i) : make_uint4(0, 0, 0, 0);
#pragma unroll 1
  for (int r0 = 0; r0 < 16; r0 += 4) {
    uint4 x[4][3];
#pragma unroll
    for (int r = 0; r < 4; r++)
#pragma unroll
      for (int i = 0; i < 3; i++)
        x[r][i] = (lane + 32 * i < 80) ? __ldg((const uint4*)(ax + (size_t)(row0 + r0 + r) * DM) + lane + 32 * i) : make_uint4(0, 0, 0, 0);
#pragma unroll
    for (int r = 0; r < 4; r++) {
      float s = 0.f;
#pragma unroll
      for (int i = 0; i < 3; i++) {
        const uint32_t xa[4] = {x[r][i].x, x[r][i].y, x[r][i].z, x[r][i].w}, wa[4] = {w[i].x, w[i].y, w[i].z, w[i].w};
#pragma unroll
        for (int q = 0; q < 4; q++) {
          s += __bfloat162float(__float2bfloat16_rn(__uint_as_float(xa[q] << 16) * __uint_as_float(wa[q] << 16)));
          s += __bfloat162float(__float2bfloat16_rn(__uint_as_float(xa[q] & 0xffff0000u) * __uint_as_float(wa[q] & 0xffff0000u)));
        }
      }
#pragma unroll
      for (int o = 16; o > 0; o >>= 1) s += __shfl_xor_sync(0xffffffffu, s, o);
      if (lane == 0) g_gate[row0 + r0 + r] = bf16r(1.0f / (1.0f + __expf(-bf16r(s))));
    }
  }
}

struct Item { int type, tt, nn, sub, ws; };
DEVINL Item decode_item(int item) {
  Item d;
  d.sub = 0; d.ws = WSPLIT;
  if (item < N_G) { d.type = 4; d.tt = item; d.nn = 0; return d; }
  item -= N_G;
  if (item < N_F1) { d.type = 0; d.tt = item / 12; d.nn = item % 12; return d; }
  item -= N_F1;
  if (item < N_F2) { d.type = 1; d.tt = item / 5; d.nn = item % 5; return d; }
  item -= N_F2;
  d.tt = min(item / N_PER_TILE, 7);
  const int q = item - d.tt * N_PER_TILE;
  if (d.tt == 7) d.ws = WSPLIT_LAST;
  if (q < N_AT_TILE) { d.type = 2; d.sub = d.tt * 8 + q / 8; d.nn = q % 8; }
  else { d.type = 3; d.nn = (q - N_AT_TILE) / d.ws; d.sub = (q - N_AT_TILE) % d.ws; }
  return d;
}

DEVINL void stage_and_store(const uint32_t (&w)[32], uint32_t stg, const CUtensorMap* tm, int col0, int row0, int cw, int wid, int lane) {
  const bool elected = (wid == 0 && lane == 0);
  if (elected) bulk_wait_read0();
  bar_sync(6 + cw, 128);
  const int ra = wid * 16 + (lane >> 2), rb = ra + 8;
#pragma unroll
  for (int t = 0; t < 16; t++) {
    const uint32_t box = stg + (t >> 3) * 8192, ch = t & 7;
    sts_u32(box + ra * 128 + ((ch ^ (ra & 7)) << 4) + 4 * (lane & 3), w[2 * t]);
    sts_u32(box + rb * 128 + ((ch ^ (rb & 7)) << 4) + 4 * (lane & 3), w[2 * t + 1]);
  }
  fence_proxy_async();
  bar_sync(6 + cw, 128);
  if (elected) {
    tma_store_2d(tm, stg, col0, row0);
    tma_store_2d(tm, stg + 8192, col0 + 64, row0);
    bulk_commit();
  }
}

__global__ void __launch_bounds__(384, 1) aux_kernel(const __grid_constant__ AuxParams p) {
  extern __shared__ __align__(1024) uint8_t smem[];
  const uint32_t sb = smem_u32(smem);
  const int tid = threadIdx.x, wg = tid >> 7, wid = (tid >> 5) & 3, lane = tid & 31;
  const uint32_t bars = sb + AUX_OFF_BAR;
  volatile int* s_items = (volatile int*)(smem + AUX_OFF_BAR + 128);
  volatile int* s_last = (volatile int*)(smem + AUX_OFF_BAR + 144);
  volatile int* s_fin = (volatile int*)(smem + AUX_OFF_BAR + 148);
  if (tid == 0) {
    for (int i = 0; i < AST; i++) { mbar_init(bars + 8 * (AB_FULL + i), 1); mbar_init(bars + 8 * (AB_EMPTY + i), 8); }
    for (int i = 0; i < 2; i++) { mbar_init(bars + 8 * (AB_QFULL + i), 1); mbar_init(bars + 8 * (AB_QEMPTY + i), 8); }
    *s_fin = 0;
    asm volatile("fence.mbarrier_init.release.cluster;" ::: "memory");
  }
  __syncthreads();
  if (wg == 0) {
    asm volatile("setmaxnreg.dec.sync.aligned.u32 40;");
    if (tid == 0) {
      uint32_t it = 0;
      for (uint32_t n = 0;; n++) {
        if (*(volatile unsigned*)&g_ctr >= (unsigned)N_TAIL_START) {
          uint32_t spin = 0;
          while (*s_fin < (int)n) { __nanosleep(64); if (++spin > (1u << 24)) __trap(); }
        }
        const int item = (int)atomicAdd(&g_ctr, 1u);
        mbar_wait(bars + 8 * (AB_QEMPTY + (n & 1)), ((n >> 1) & 1) ^ 1);
        s_items[n & 1] = item;
        mbar_arrive(bars + 8 * (AB_QFULL + (n & 1)));
        if (item >= N_ITEMS) break;
        const Item d = decode_item(item);
        if (d.type == 1) { wait_flag(&g_f1flag[2 * d.tt], 24); wait_flag(&g_f1flag[2 * d.tt + 1], 24); }
        if (d.type == 2) wait_flag(&g_segflag[d.sub], 288);
        if (d.type == 3) wait_flag(&g_atflag[d.tt], 256);
        fence_proxy_async_all();
        const int nk = (d.type == 0) ? 10 : (d.type == 1 ? 24 : (d.type == 2 ? 4 : (d.type == 3 ? 96 / d.ws : 0)));
        for (int k = 0; k < nk; k++, it++) {
          const uint32_t st = it % AST, ph = (it / AST) & 1;
          mbar_wait(bars + 8 * (AB_EMPTY + st), ph ^ 1);
          const uint32_t a = sb + st * AST_BYTES, fb = bars + 8 * (AB_FULL + st);
          if (d.type == 0) {
            mbar_arrive_expect_tx(fb, 49152);
            tma_load_2d(a, &p.tm_x128, k * 64, d.tt * 128, fb);
            tma_load_2d(a + 16384, &p.tm_wg, d.nn * 128, k * 64, fb);
            tma_load_2d(a + 24576, &p.tm_wg, d.nn * 128 + 64, k * 64, fb);
            tma_load_2d(a + 32768, &p.tm_wu, d.nn * 128, k * 64, fb);
            tma_load_2d(a + 40960, &p.tm_wu, d.nn * 128 + 64, k * 64, fb);
          } else if (d.type == 2) {
            const int h = d.nn * 4 + k;
            mbar_arrive_expect_tx(fb, 12288 + 15360 + 15360);
            for (int c = 0; c < 3; c++) {
              tma_load_2d(a + c * 4096, &p.tm_q, h * DH + c * 64, d.sub * SEG, fb);
              tma_load_2d(a + 12288 + c * 5120, &p.tm_k, h * DH + c * 64, d.sub * 40, fb);
            }
            tma_load_2d(a + 27648, &p.tm_v3, 0, (d.sub * NH + h) * DH, fb);
          } else {
            const int kk = (d.type == 3 ? d.sub * (96 / d.ws) : 0) + k;
            const CUtensorMap* ta = d.type == 1 ? &p.tm_hid : &p.tm_o;
            const CUtensorMap* tb = d.type == 1 ? &p.tm_wd : &p.tm_wo;
            mbar_arrive_expect_tx(fb, 49152);
            tma_load_2d(a, ta, kk * 64, d.tt * 256, fb);
            tma_load_2d(a + 16384, ta, kk * 64, d.tt * 256 + 128, fb);
            tma_load_2d(a + 32768, tb, d.nn * 128, kk * 64, fb);
            tma_load_2d(a + 40960, tb, d.nn * 128 + 64, kk * 64, fb);
          }
        }
      }
    }
  } else {
    asm volatile("setmaxnreg.inc.sync.aligned.u32 232;");
    const int cw = wg - 1, ct = tid - 128;
    uint32_t it = 0;
    for (uint32_t n = 0;; n++) {
      mbar_wait(bars + 8 * (AB_QFULL + (n & 1)), (n >> 1) & 1);
      const int item = s_items[n & 1];
      __syncwarp();
      if (lane == 0) mbar_arrive(bars + 8 * (AB_QEMPTY + (n & 1)));
      if (item >= N_ITEMS) break;
      const Item d = decode_item(item);

      if (d.type != 2 && d.type != 4) {
        const bool f1like = (d.type == 0);
        const int nk = f1like ? 10 : (d.type == 1 ? 24 : 96 / d.ws);
        float acc0[64], acc1[64];
        const uint32_t a0o = f1like ? cw * 8192 : cw * 16384, a1o = f1like ? a0o : a0o + 8192;
        const uint32_t b0o = f1like ? 16384 : 32768, b1o = 32768;
        for (int k = 0; k < nk; k++, it++) {
          const uint32_t st = it % AST, ph = (it / AST) & 1;
          mbar_wait(bars + 8 * (AB_FULL + st), ph);
          const uint32_t s0 = sb + st * AST_BYTES;
          wg_fence();
#pragma unroll
          for (int kk = 0; kk < 4; kk++) {
            wgmma_n128_tB(acc0, make_desc(s0 + a0o + kk * 32, 16, 1024, 1), make_desc(s0 + b0o + kk * 2048, 8192, 1024, 1), (k | kk) != 0);
            wgmma_n128_tB(acc1, make_desc(s0 + a1o + kk * 32, 16, 1024, 1), make_desc(s0 + b1o + kk * 2048, 8192, 1024, 1), (k | kk) != 0);
          }
          wg_commit();
          if (k > 0) {
            wg_wait<1>();
            if (lane == 0) mbar_arrive(bars + 8 * (AB_EMPTY + (it - 1) % AST));
          }
        }
        wg_wait<0>();
        if (lane == 0) mbar_arrive(bars + 8 * (AB_EMPTY + (it - 1) % AST));

        const uint32_t stg = sb + AUX_OFF_STG + cw * 16384;
        const bool elected = (wid == 0 && lane == 0);
        uint32_t w[32];
        if (d.type == 0) {
#pragma unroll
          for (int t = 0; t < 16; t++) {
            float h00 = bf16r(sigmoidf_(bf16r(acc0[4 * t + 0]))) * bf16r(acc1[4 * t + 0]);
            float h01 = bf16r(sigmoidf_(bf16r(acc0[4 * t + 1]))) * bf16r(acc1[4 * t + 1]);
            float h10 = bf16r(sigmoidf_(bf16r(acc0[4 * t + 2]))) * bf16r(acc1[4 * t + 2]);
            float h11 = bf16r(sigmoidf_(bf16r(acc0[4 * t + 3]))) * bf16r(acc1[4 * t + 3]);
            w[2 * t] = pack_bf16(h00, h01);
            w[2 * t + 1] = pack_bf16(h10, h11);
          }
          stage_and_store(w, stg, &p.tm_hst, d.nn * 128, d.tt * 128 + cw * 64, cw, wid, lane);
          if (elected) { bulk_wait0(); red_relaxed_add(&g_f1flag[d.tt], 1); }
        } else {
          const int row0 = d.tt * 256 + cw * 128;
          const int tile = d.tt * 5 + d.nn;
          bool fin = true;
          if (d.type == 3) {
            const size_t slot0 = (tile < 35) ? (size_t)tile * WSPLIT : (size_t)35 * WSPLIT + (size_t)(tile - 35) * WSPLIT_LAST;
            float4* mine = (float4*)(g_wpart + (slot0 + d.sub) * 32768) + ct;
#pragma unroll
            for (int t = 0; t < 16; t++) {
              __stcg(mine + t * 256, make_float4(acc0[4 * t], acc0[4 * t + 1], acc0[4 * t + 2], acc0[4 * t + 3]));
              __stcg(mine + (16 + t) * 256, make_float4(acc1[4 * t], acc1[4 * t + 1], acc1[4 * t + 2], acc1[4 * t + 3]));
            }
            bar_sync(1, 256);
            if (ct == 0) {
              unsigned old;
              asm volatile("atom.acq_rel.gpu.global.add.u32 %0, [%1], 1;" : "=r"(old) : "l"(&g_wcnt[tile]) : "memory");
              *s_last = (int)old;
              if (d.ws == WSPLIT_LAST) { wait_flag(&g_wcnt[tile], WSPLIT_LAST); wait_flag(&g_f2flag[tile], 1); }
              else if (old == (unsigned)d.ws - 1) wait_flag(&g_f2flag[tile], 1);
            }
            bar_sync(1, 256);
            fin = (*s_last == d.ws - 1);
            bar_sync(1, 256);
            if (d.ws == WSPLIT_LAST) {
              fin = false;
              const int v0 = d.sub * 2, half = v0 >> 4, t0 = v0 & 15;
              const float4* src = (const float4*)(g_wpart + slot0 * 32768) + v0 * 256 + ct;
              float4 sum[2];
#pragma unroll
              for (int q = 0; q < 2; q++) sum[q] = make_float4(0.f, 0.f, 0.f, 0.f);
#pragma unroll
              for (int o = 0; o < WSPLIT_LAST; o++)
#pragma unroll
                for (int q = 0; q < 2; q++) {
                  const float4 v = __ldcg(src + o * 8192 + q * 256);
                  sum[q].x += v.x; sum[q].y += v.y; sum[q].z += v.z; sum[q].w += v.w;
                }
              const int rr = row0 + 64 * half + wid * 16 + (lane >> 2);
              const float ga = __ldcg(&g_gate[rr]), gb = __ldcg(&g_gate[rr + 8]);
              const uint4 b0 = __ldcg(g_bfrag + (size_t)tile * 16 * 256 + (8 * half + (t0 >> 1)) * 256 + ct);
              const uint32_t bb[4] = {b0.x, b0.y, b0.z, b0.w};
              __nv_bfloat16* dst = p.out + (size_t)rr * DM + d.nn * 128 + t0 * 8 + 2 * (lane & 3);
#pragma unroll
              for (int q = 0; q < 2; q++) {
                *(uint32_t*)(dst + 8 * q) = pack_bf16(bf16r(ga * bf16r(sum[q].x)) + __uint_as_float(bb[2 * q] << 16),
                                                      bf16r(ga * bf16r(sum[q].y)) + __uint_as_float(bb[2 * q] & 0xffff0000u));
                *(uint32_t*)(dst + 8 * DM + 8 * q) = pack_bf16(bf16r(gb * bf16r(sum[q].z)) + __uint_as_float(bb[2 * q + 1] << 16),
                                                               bf16r(gb * bf16r(sum[q].w)) + __uint_as_float(bb[2 * q + 1] & 0xffff0000u));
              }
            }
            if (fin) {
#pragma unroll 1
              for (int o = 0; o < d.ws; o++) {
                if (o != d.sub) {
                  const float4* other = (const float4*)(g_wpart + (slot0 + o) * 32768) + ct;
#pragma unroll
                  for (int t = 0; t < 16; t++) {
                    float4 v = __ldcg(other + t * 256), u = __ldcg(other + (16 + t) * 256);
                    acc0[4 * t] += v.x; acc0[4 * t + 1] += v.y; acc0[4 * t + 2] += v.z; acc0[4 * t + 3] += v.w;
                    acc1[4 * t] += u.x; acc1[4 * t + 1] += u.y; acc1[4 * t + 2] += u.z; acc1[4 * t + 3] += u.w;
                  }
                }
              }
            }
          } else {
            if (ct == 0) { wait_flag(&g_gflag[2 * d.tt], 1); wait_flag(&g_gflag[2 * d.tt + 1], 1); }
            bar_sync(1, 256);
          }
          if (fin) {
            const int rr = row0 + wid * 16 + (lane >> 2);
            const float g0 = __ldcg(&g_gate[rr]), g1 = __ldcg(&g_gate[rr + 8]), g2 = __ldcg(&g_gate[rr + 64]), g3 = __ldcg(&g_gate[rr + 72]);
            uint4* bf = g_bfrag + (size_t)tile * 16 * 256 + ct;
            if (d.type == 1) {
              const float m0 = bf16r(1.0f - g0), m1 = bf16r(1.0f - g1), m2 = bf16r(1.0f - g2), m3 = bf16r(1.0f - g3);
#pragma unroll
              for (int t = 0; t < 8; t++) {
                uint4 v, u;
                v.x = pack_bf16(m0 * bf16r(acc0[8 * t + 0]), m0 * bf16r(acc0[8 * t + 1])); v.y = pack_bf16(m1 * bf16r(acc0[8 * t + 2]), m1 * bf16r(acc0[8 * t + 3]));
                v.z = pack_bf16(m0 * bf16r(acc0[8 * t + 4]), m0 * bf16r(acc0[8 * t + 5])); v.w = pack_bf16(m1 * bf16r(acc0[8 * t + 6]), m1 * bf16r(acc0[8 * t + 7]));
                u.x = pack_bf16(m2 * bf16r(acc1[8 * t + 0]), m2 * bf16r(acc1[8 * t + 1])); u.y = pack_bf16(m3 * bf16r(acc1[8 * t + 2]), m3 * bf16r(acc1[8 * t + 3]));
                u.z = pack_bf16(m2 * bf16r(acc1[8 * t + 4]), m2 * bf16r(acc1[8 * t + 5])); u.w = pack_bf16(m3 * bf16r(acc1[8 * t + 6]), m3 * bf16r(acc1[8 * t + 7]));
                __stcg(bf + t * 256, v);
                __stcg(bf + (8 + t) * 256, u);
              }
              bar_sync(1, 256);
              if (ct == 0) { red_release_add(&g_f2flag[tile], 1); }
            } else {
#pragma unroll
              for (int half = 0; half < 2; half++) {
                const float* acc = half ? acc1 : acc0;
                const float ga = half ? g2 : g0, gb = half ? g3 : g1;
                uint4 bv[8];
#pragma unroll
                for (int t = 0; t < 8; t++) bv[t] = __ldcg(bf + (8 * half + t) * 256);
#pragma unroll
                for (int t = 0; t < 8; t++) {
                  const uint32_t bb[4] = {bv[t].x, bv[t].y, bv[t].z, bv[t].w};
#pragma unroll
                  for (int q = 0; q < 4; q++) {
                    const float gg = (q & 1) ? gb : ga;
                    const float lo = bf16r(gg * bf16r(acc[8 * t + 2 * q])) + __uint_as_float(bb[q] << 16);
                    const float hi = bf16r(gg * bf16r(acc[8 * t + 2 * q + 1])) + __uint_as_float(bb[q] & 0xffff0000u);
                    w[4 * t + q] = pack_bf16(lo, hi);
                  }
                }
                stage_and_store(w, stg, &p.tm_out, d.nn * 128, row0 + 64 * half, cw, wid, lane);
              }
            }
          }
        }
      } else if (d.type == 4) {
        gate_rows(p.ax, p.gate_w, d.tt * 128 + (cw * 4 + wid) * 16, lane);
        bar_sync(1, 256);
        if (ct == 0) red_release_add(&g_gflag[d.tt], 1);
      } else {
        const int w8 = cw * 4 + wid, pr = w8 >> 1, mt = w8 & 1;
        {
          const uint32_t my = it + pr, st = my % AST, ph = (my / AST) & 1;
          const uint32_t base = sb + st * AST_BYTES;
          mbar_wait(bars + 8 * (AB_FULL + st), ph);
          const int r8 = lane & 7;
          float S[5][4];
#pragma unroll
          for (int t = 0; t < 5; t++) S[t][0] = S[t][1] = S[t][2] = S[t][3] = 0.f;
#pragma unroll
          for (int c = 0; c < 3; c++) {
#pragma unroll
            for (int kk = 0; kk < 4; kk++) {
              uint32_t a[4];
              {
                int row = mt * 16 + (lane & 15), ch = 2 * kk + (lane >> 4);
                ldsm_x4(a, base + c * 4096 + row * 128 + ((ch ^ (row & 7)) << 4));
              }
#pragma unroll
              for (int t = 0; t < 5; t++) {
                uint32_t b0, b1;
                int row = 8 * t + r8, ch = 2 * kk + ((lane >> 3) & 1);
                ldsm_x2(b0, b1, base + 12288 + c * 5120 + row * 128 + ((ch ^ (row & 7)) << 4));
                mma16816(S[t], a[0], a[1], a[2], a[3], b0, b1);
              }
            }
          }
          const float sc = 0.07216878364870322f * 1.4426950408889634f;
          const int q0 = mt * 16 + (lane >> 2), q1 = q0 + 8;
          float m0 = -1e30f, m1 = -1e30f;
#pragma unroll
          for (int t = 0; t < 5; t++) {
#pragma unroll
            for (int e = 0; e < 2; e++) {
              int key = 8 * t + 2 * (lane & 3) + e - 8;
              if (key > q0) S[t][e] = -1e30f;
              if (key > q1) S[t][2 + e] = -1e30f;
              m0 = fmaxf(m0, S[t][e]);
              m1 = fmaxf(m1, S[t][2 + e]);
            }
          }
          m0 = fmaxf(m0, __shfl_xor_sync(0xffffffffu, m0, 1)); m0 = fmaxf(m0, __shfl_xor_sync(0xffffffffu, m0, 2));
          m1 = fmaxf(m1, __shfl_xor_sync(0xffffffffu, m1, 1)); m1 = fmaxf(m1, __shfl_xor_sync(0xffffffffu, m1, 2));
          float s0 = 0.f, s1 = 0.f;
#pragma unroll
          for (int t = 0; t < 5; t++) {
#pragma unroll
            for (int e = 0; e < 2; e++) {
              S[t][e] = ex2f((S[t][e] - m0) * sc); s0 += S[t][e];
              S[t][2 + e] = ex2f((S[t][2 + e] - m1) * sc); s1 += S[t][2 + e];
            }
          }
          s0 += __shfl_xor_sync(0xffffffffu, s0, 1); s0 += __shfl_xor_sync(0xffffffffu, s0, 2);
          s1 += __shfl_xor_sync(0xffffffffu, s1, 1); s1 += __shfl_xor_sync(0xffffffffu, s1, 2);
          const float i0 = 1.0f / s0, i1 = 1.0f / s1;
          uint32_t P0[5], P1[5];
#pragma unroll
          for (int t = 0; t < 5; t++) { P0[t] = pack_bf16(S[t][0] * i0, S[t][1] * i0); P1[t] = pack_bf16(S[t][2] * i1, S[t][3] * i1); }
          __syncwarp();
#pragma unroll 4
          for (int nt = 0; nt < 24; nt++) {
            uint32_t b[4], b4;
            const uint32_t vb = base + 27648 + (8 * nt + r8) * 80;
            ldsm_x4(b, vb + (lane >> 3) * 16);
            ldsm_x1(b4, vb + 64);
            float o[4] = {0, 0, 0, 0}, o2[4] = {0, 0, 0, 0};
            mma16816(o, P0[0], P1[0], P0[1], P1[1], b[0], b[1]);
            mma16816(o2, P0[2], P1[2], P0[3], P1[3], b[2], b[3]);
            mma1688(o, P0[4], P1[4], b4);
            const int c = nt >> 3, ch = nt & 7;
            const int ra = mt * 16 + (lane >> 2), rb = ra + 8;
            sts_u32(base + c * 4096 + ra * 128 + ((ch ^ (ra & 7)) << 4) + 4 * (lane & 3), pack_bf16(o[0] + o2[0], o[1] + o2[1]));
            sts_u32(base + c * 4096 + rb * 128 + ((ch ^ (rb & 7)) << 4) + 4 * (lane & 3), pack_bf16(o[2] + o2[2], o[3] + o2[3]));
          }
          fence_proxy_async();
          bar_sync(2 + pr, 64);
          if (mt == 0 && lane == 0) {
            const int h = d.nn * 4 + pr;
            for (int c = 0; c < 3; c++) tma_store_2d(&p.tm_ost, base + c * 4096, h * DH + c * 64, d.sub * SEG);
            bulk_commit();
            bulk_wait_read0();
            mbar_arrive_cnt(bars + 8 * (AB_EMPTY + st), 8);
            bulk_wait0();
            red_relaxed_add(&g_atflag[d.tt], 1);
          }
        }
        it += 4;
      }
      if (item >= N_TAIL_START - 72) bar_sync(1, 256);
      if (ct == 0) *s_fin = (int)n + 1;

    }
  }
  if (wg > 0 && wid == 0 && lane == 0) bulk_wait0();
  __syncwarp();
  if (tid == 0) asm volatile("griddepcontrol.wait;" ::: "memory");
  __syncthreads();
  if (tid == 0) {
    unsigned old;
    asm volatile("atom.acq_rel.gpu.global.add.u32 %0, [%1], 1;" : "=r"(old) : "l"(&g_done) : "memory");
    s_items[0] = (old == gridDim.x - 1);
  }
  __syncthreads();
  if (s_items[0]) {
    for (int k = tid; k < (int)(H2_SLOT / 16); k += 384) g_xch[(H2_BASE + ((NSEG - 2) % NSLOT) * H2_SLOT) / 16 + k] = make_uint4(0, 0, 0, 0);
    if (tid < NSEG) g_segflag[tid] = 0;
    if (tid < 16) { g_f1flag[tid] = 0; g_gflag[tid] = 0; }
    if (tid < 8) g_atflag[tid] = 0;
    if (tid < 40) { g_f2flag[tid] = 0; g_wcnt[tid] = 0; }
    if (tid == 0) { g_ctr = 0; g_done = 0; }
  }
}


typedef CUresult (*PFN_encodeTiled)(CUtensorMap*, CUtensorMapDataType, cuuint32_t, void*, const cuuint64_t*, const cuuint64_t*,
                                    const cuuint32_t*, const cuuint32_t*, CUtensorMapInterleave, CUtensorMapSwizzle,
                                    CUtensorMapL2promotion, CUtensorMapFloatOOBfill);
static PFN_encodeTiled get_encode() {
  static PFN_encodeTiled fn = nullptr;
  if (!fn) {
    void* f = nullptr;
    cudaDriverEntryPointQueryResult qr;
    cudaGetDriverEntryPoint("cuTensorMapEncodeTiled", &f, cudaEnableDefault, &qr);
    fn = (PFN_encodeTiled)f;
  }
  return fn;
}
static void make_tm(CUtensorMap* tm, const void* ptr, uint64_t rows, uint64_t cols, uint64_t pitch_elems, uint32_t brows,
                    uint32_t bcols, CUtensorMapSwizzle swz) {
  cuuint64_t dims[2] = {cols, rows};
  cuuint64_t strides[1] = {pitch_elems * 2};
  cuuint32_t box[2] = {bcols, brows};
  cuuint32_t es[2] = {1, 1};
  get_encode()(tm, CU_TENSOR_MAP_DATA_TYPE_BFLOAT16, 2, (void*)ptr, dims, strides, box, es, CU_TENSOR_MAP_INTERLEAVE_NONE, swz,
               CU_TENSOR_MAP_L2_PROMOTION_L2_256B, CU_TENSOR_MAP_FLOAT_OOB_FILL_NONE);
}

static MainParams mp;
static AuxParams ap;
extern "C" void kernel_launch(void* const* d_in, const int* in_sizes, int n_in, void* d_out, int out_size) {
  static int n_sm = 0;
  static void* last_in[12] = {};
  bool fresh = (n_sm == 0);
  for (int i = 0; i < 12 && i < n_in; i++) fresh = fresh || (last_in[i] != d_in[i]);
  if (fresh) {
    for (int i = 0; i < 12 && i < n_in; i++) last_in[i] = d_in[i];
    void *q, *k, *v, *hid, *o;
    cudaGetSymbolAddress(&q, g_q);
    cudaGetSymbolAddress(&k, g_k);
    cudaGetSymbolAddress(&v, g_vT);
    cudaGetSymbolAddress(&hid, g_hid);
    cudaGetSymbolAddress(&o, g_o);
    const CUtensorMapSwizzle S128 = CU_TENSOR_MAP_SWIZZLE_128B, S0 = CU_TENSOR_MAP_SWIZZLE_NONE;
    make_tm(&mp.tm_x, d_in[0], SEQ, DM, DM, 32, 64, S128);
    make_tm(&mp.tm_wv, d_in[4], DM, HD, HD, 128, 64, S128);
    make_tm(&mp.tm_wq, d_in[2], DM, HD, HD, 128, 64, S128);
    make_tm(&mp.tm_wk, d_in[3], DM, HD, HD, 128, 64, S128);
    make_tm(&mp.tm_wo, d_in[5], HD, DM, DM, 64, 64, S128);
    make_tm(&mp.tm_q, q, SEQ, HD, HD, 32, 64, S128);
    make_tm(&mp.tm_k, k, NSEG * 40, HD, HD, 40, 64, S128);
    make_tm(&mp.tm_v, v, (uint64_t)NSEG * HD, 40, 40, 64, 40, S0);
    mp.mem0 = (const __nv_bfloat16*)d_in[1];
    mp.d1 = 400; mp.d2 = 500; mp.d3 = 1500;
    make_tm(&ap.tm_x128, d_in[0], SEQ, DM, DM, 128, 64, S128);
    make_tm(&ap.tm_wg, d_in[8], DM, FF, FF, 64, 64, S128);
    make_tm(&ap.tm_wu, d_in[9], DM, FF, FF, 64, 64, S128);
    make_tm(&ap.tm_hid, hid, SEQ, FF, FF, 128, 64, S128);
    make_tm(&ap.tm_wd, d_in[10], FF, DM, DM, 64, 64, S128);
    make_tm(&ap.tm_o, o, SEQ, HD, HD, 128, 64, S128);
    ap.tm_wo = mp.tm_wo;
    ap.tm_q = mp.tm_q;
    ap.tm_k = mp.tm_k;
    make_tm(&ap.tm_v3, v, (uint64_t)NSEG * HD, 40, 40, 192, 40, S0);
    make_tm(&ap.tm_ost, o, SEQ, HD, HD, 32, 64, S128);
    make_tm(&ap.tm_hst, hid, SEQ, FF, FF, 64, 64, S128);
    ap.ax = (const __nv_bfloat16*)d_in[0];
    ap.gate_w = (const __nv_bfloat16*)d_in[11];
    cudaFuncSetAttribute(main_kernel, cudaFuncAttributeMaxDynamicSharedMemorySize, MAIN_SMEM);
    cudaFuncSetAttribute(aux_kernel, cudaFuncAttributeMaxDynamicSharedMemorySize, AUX_SMEM);
    cudaDeviceGetAttribute(&n_sm, cudaDevAttrMultiProcessorCount, 0);
  }
  static void* last_out = nullptr;
  if (last_out != d_out) {
    make_tm(&ap.tm_out, d_out, SEQ, DM, DM, 64, 64, CU_TENSOR_MAP_SWIZZLE_128B);
    ap.out = (__nv_bfloat16*)d_out;
    last_out = d_out;
  }
  (void)in_sizes; (void)out_size;
  cudaStream_t st = cudaStreamPerThread;
  {
    cudaLaunchConfig_t cfg = {};
    cfg.gridDim = dim3(96);
    cfg.blockDim = dim3(512);
    cfg.dynamicSmemBytes = MAIN_SMEM;
    cfg.stream = st;
    cudaLaunchAttribute at[1];
    at[0].id = cudaLaunchAttributeClusterDimension;
    at[0].val.clusterDim.x = 3; at[0].val.clusterDim.y = 1; at[0].val.clusterDim.z = 1;
    cfg.attrs = at;
    cfg.numAttrs = 1;
    cudaLaunchKernelEx(&cfg, main_kernel, mp);
  }
  {
    cudaLaunchConfig_t cfg = {};
    cfg.gridDim = dim3(n_sm);
    cfg.blockDim = dim3(384);
    cfg.dynamicSmemBytes = AUX_SMEM;
    cfg.stream = st;
    cudaLaunchAttribute at[1];
    at[0].id = cudaLaunchAttributeProgrammaticStreamSerialization;
    at[0].val.programmaticStreamSerializationAllowed = 1;
    cfg.attrs = at;
    cfg.numAttrs = 1;
    cudaLaunchKernelEx(&cfg, aux_kernel, ap);
  }
}
```
